```python
import torch

def _softmax(x, axis=-1):
    return torch.softmax(x, dim=axis)
def _gelu(x):
    return torch.nn.functional.gelu(x, approximate="tanh")
def _silu(x):
    return torch.nn.functional.silu(x)
def _sigmoid(x):
    return torch.sigmoid(x)
def _layernorm(x, axis=-1, eps=1e-5):
    m = x.mean(dim=axis, keepdim=True)
    v = x.var(dim=axis, keepdim=True, unbiased=False)
    return (x - m) / torch.sqrt(v + eps)
def _scatter_add(tgt, idx, src, axis=0):
    return tgt.clone().index_add_(axis, idx, src)
def _segment_sum(src, seg, n):
    out = torch.zeros((n,) + src.shape[1:], dtype=src.dtype)
    return out.index_add_(0, seg, src)
def _pad(x, pw):
    flat = tuple(v for pair in reversed(pw) for v in pair)
    return torch.nn.functional.pad(x, flat)

kernel_name = 'recurrent_scan__mha_block_cached__mixer_token_mlp__prompt'

def setup_inputs():

    _w = (lambda a: (lambda t: t.to(torch.bfloat16) if t.is_floating_point() else t)(torch.as_tensor(a)))
    def _A_setup():
        B, Sq, D = 1, 2048, 640
        H, Sk, Dh = 32, 2048, 128
        return {
            "x": _w((lambda *s: torch.randn(*s, dtype=torch.bfloat16) * 0.1)(B, Sq, D)),
            "k_cache": _w((lambda *s: torch.randn(*s, dtype=torch.bfloat16) * 0.8)(B, H, Sk, Dh)),
            "v_cache": _w((lambda *s: torch.randn(*s, dtype=torch.bfloat16) * 3.2)(B, H, Sk, Dh)),
            "wq": _w((lambda *s: torch.randn(*s, dtype=torch.bfloat16) * 0.8)(D, H * Dh) * (D ** -0.5)),
            "wo": _w((lambda *s: torch.randn(*s, dtype=torch.bfloat16) * 3.2)(H * Dh, D) * ((H * Dh) ** -0.5)),
        }
    _A_in = _A_setup()

    def _B_setup():
        B, S, D, F = 1, 2048, 640, 1728
        return {
            "x": _w((lambda *s: torch.randn(*s, dtype=torch.bfloat16) * 0.1)(B, S, D)),
            "w1": _w((lambda *s: torch.randn(*s, dtype=torch.bfloat16) * 3.2)(S, F) * (S ** -0.5)),
            "b1": _w((lambda *s: torch.randn(*s, dtype=torch.bfloat16) * 3.2)(F) * 0.02),
            "w2": _w((lambda *s: torch.randn(*s, dtype=torch.bfloat16) * 3.2)(F, S) * (F ** -0.5)),
            "b2": _w((lambda *s: torch.randn(*s, dtype=torch.bfloat16) * 3.2)(S) * 0.02),
        }
    _B_in = _B_setup()

    return {
        "A_x": _A_in["x"],
        "A_k_cache": _A_in["k_cache"],
        "A_v_cache": _A_in["v_cache"],
        "A_wq": _A_in["wq"],
        "A_wo": _A_in["wo"],
        "B_x": _B_in["x"],
        "B_w1": _B_in["w1"],
        "B_b1": _B_in["b1"],
        "B_w2": _B_in["w2"],
        "B_b2": _B_in["b2"],
    }

def reference(A_x, A_k_cache, A_v_cache, A_wq, A_wo, B_x, B_w1, B_b1, B_w2, B_b2):
    def _A_ref(x, k_cache, v_cache, wq, wo):
        B, Sq, D = x.shape
        H, Dh = 32, 128
        q = (lambda x, *d: x.permute(*d))((x @ wq).reshape(B, Sq, H, Dh), 0, 2, 1, 3)
        scores = torch.einsum("bhqd,bhkd->bhqk", q, k_cache) * (Dh ** -0.5)
        p = _softmax(scores, axis=-1)
        o = torch.einsum("bhqk,bhkd->bhqd", p, v_cache)
        return (lambda x, *d: x.permute(*d))(o, 0, 2, 1, 3).reshape(B, Sq, H * Dh) @ wo

    def _B_ref(x, w1, b1, w2, b2):
        B, S, D = x.shape
        h = _layernorm(x, axis=-1)
        u = torch.einsum("bsd,sf->bdf", h, w1) + b1
        u = _gelu(u)
        y = torch.einsum("bdf,fs->bds", u, w2) + b2
        return (lambda x, *d: x.permute(*d))(y, 0, 2, 1)

    x = A_x
    xn = _layernorm(x, axis=-1)
    s = _A_ref(xn, A_k_cache, A_v_cache, A_wq, A_wo)
    g = _silu(_B_ref(xn, B_w1, B_b1, B_w2, B_b2))
    return x + s * g
```

```cpp
#include <cuda_runtime.h>
#include <cuda_bf16.h>
#include <cuda.h>
#include <stdint.h>
#include <string.h>

typedef __nv_bfloat16 bf16;

namespace {

constexpr int SEQ = 2048, DM = 640, NH = 32, DH = 128, FF = 1728, HD = NH * DH;
constexpr int STAGE_BYTES = 32768;
constexpr int NSTAGE = 5;
constexpr int QB1_OFF = NSTAGE * STAGE_BYTES;
constexpr int QB0_OFF = QB1_OFF + STAGE_BYTES;
constexpr int BAR_OFF = QB0_OFF + STAGE_BYTES;
constexpr int SMEM_BYTES = BAR_OFF + 256 + 1024;
constexpr int NCLUSTER = 66, MAXITEMS = 8;

__device__ __align__(1024) bf16 g_xn[SEQ * DM];
__device__ __align__(1024) bf16 g_h[SEQ * DM];
__device__ __align__(1024) bf16 g_o[SEQ * HD];
__device__ __align__(1024) bf16 g_ut[FF * DM];
__device__ __align__(1024) uint4 g_gfrag[SEQ * DM / 8];
__device__ unsigned g_epoch[2 * NCLUSTER * 8];
__device__ unsigned g_cnt_ln[32 * 32];
__device__ unsigned g_cnt_o[16 * 32];
__device__ unsigned g_cnt_u[7 * 32];
__device__ unsigned g_cnt_g[32 * 2];

#define TL(slot) do {} while (0)
#define FT(slot) do {} while (0)
#define TLX(w, slot) do {} while (0)

struct alignas(64) Params {
  CUtensorMap tm_xn;
  CUtensorMap tm_wq;
  CUtensorMap tm_k;
  CUtensorMap tm_v;
  CUtensorMap tm_o_st;
  CUtensorMap tm_o_ld;
  CUtensorMap tm_wo;
  CUtensorMap tm_w1;
  CUtensorMap tm_h;
  CUtensorMap tm_ut_st;
  CUtensorMap tm_ut;
  CUtensorMap tm_w2;
  CUtensorMap tm_out;
  CUtensorMap tm_w2b;
  const bf16* x;
  const bf16* b1;
  const bf16* b2;
  const bf16 *w1, *w2, *wo, *wq, *kc, *vc;
  uint16_t items[NCLUSTER * MAXITEMS];
  uint8_t horder[8 * 32];
};

__device__ __forceinline__ uint32_t smem_u32(const void* p) { return (uint32_t)__cvta_generic_to_shared(p); }
__device__ __forceinline__ void mbar_init(uint32_t bar, uint32_t cnt) {
  asm volatile("mbarrier.init.shared::cta.b64 [%0], %1;" ::"r"(bar), "r"(cnt));
}
__device__ __forceinline__ void mbar_expect_tx(uint32_t bar, uint32_t bytes) {
  asm volatile("mbarrier.arrive.expect_tx.shared::cta.b64 _, [%0], %1;" ::"r"(bar), "r"(bytes) : "memory");
}
__device__ __forceinline__ void mbar_wait(uint32_t bar, uint32_t parity) {
  asm volatile(
      "{\n.reg .pred p;\n.reg .u32 n;\n"
      "mbarrier.try_wait.parity.shared::cta.b64 p, [%0], %1;\n"
      "@p bra MW_DONE;\n"
      "mov.u32 n, 0;\n"
      "MW_LOOP:\n"
      "mbarrier.try_wait.parity.shared::cta.b64 p, [%0], %1;\n"
      "@p bra MW_DONE;\n"
      "add.u32 n, n, 1;\n"
      "setp.lt.u32 p, n, 4194304;\n"
      "@p bra MW_LOOP;\n"
      "trap;\n"
      "MW_DONE:\n}\n" ::"r"(bar), "r"(parity) : "memory");
}
__device__ __forceinline__ void red_release(unsigned* p, unsigned v) {
  asm volatile("red.release.gpu.global.add.u32 [%0], %1;" ::"l"(p), "r"(v) : "memory");
}
__device__ __forceinline__ void flag_wait(const unsigned* ptr, unsigned target) {
  asm volatile(
      "{\n.reg .pred p;\n.reg .u32 n, v;\n.reg .s32 d;\n"
      "mov.u32 n, 0;\n"
      "FW_LOOP:\n"
      "ld.acquire.gpu.global.u32 v, [%0];\n"
      "sub.s32 d, v, %1;\n"
      "setp.ge.s32 p, d, 0;\n"
      "@p bra FW_DONE;\n"
      "nanosleep.u32 100;\n"
      "add.u32 n, n, 1;\n"
      "setp.lt.u32 p, n, 4194304;\n"
      "@p bra FW_LOOP;\n"
      "trap;\n"
      "FW_DONE:\n"
      "fence.proxy.async.global;\n}\n" ::"l"(ptr), "r"(target) : "memory");
}
__device__ __forceinline__ uint32_t mask_wait(uint32_t have, uint32_t need, uint32_t watch, const unsigned* lane_ptr, unsigned target) {
  if ((have & need) == need) return have;
  const uint32_t me = (watch >> (threadIdx.x & 31)) & 1;
#pragma unroll 1
  for (uint32_t n = 0;; n++) {
    unsigned v = target - 1;
    asm volatile("{\n.reg .pred p;\nsetp.ne.u32 p, %2, 0;\n@p ld.acquire.gpu.global.u32 %0, [%1];\n}\n" : "+r"(v) : "l"(lane_ptr), "r"(me) : "memory");
    have |= __ballot_sync(0xffffffffu, (int)(v - target) >= 0);
    if ((have & need) == need) break;
    asm volatile("{\n.reg .pred p;\nsetp.gt.u32 p, %0, 4194304;\n@p trap;\nnanosleep.u32 20;\n}\n" ::"r"(n));
  }
  asm volatile("fence.proxy.async.global;" ::: "memory");
  __syncwarp();
  return have;
}
__device__ __forceinline__ void l2_prefetch(const void* ptr) {
  asm volatile("cp.async.bulk.prefetch.L2.global [%0], 4096;" ::"l"(ptr) : "memory");
}
__device__ __forceinline__ void prefetch_all(const void* base, uint32_t total, uint32_t gap) {
#pragma unroll 1
  for (uint32_t off = blockIdx.x * 4096; off < total; off += 2 * NCLUSTER * 4096) {
    l2_prefetch((const char*)base + off);
    __nanosleep(gap);
  }
}
__device__ __forceinline__ void mbar_arrive_local(uint32_t bar) {
  asm volatile("mbarrier.arrive.shared::cta.b64 _, [%0];" ::"r"(bar) : "memory");
}
__device__ __forceinline__ void tma_prefetch(const CUtensorMap* tm, int c0, int c1) {
  asm volatile("cp.async.bulk.prefetch.tensor.2d.L2.global [%0, {%1, %2}];" ::"l"(tm), "r"(c0), "r"(c1) : "memory");
}
__device__ __forceinline__ void mbar_arrive_mapped(uint32_t mapped_bar) {
  asm volatile("mbarrier.arrive.shared::cluster.b64 _, [%0];" ::"r"(mapped_bar) : "memory");
}
__device__ __forceinline__ uint32_t mapa(uint32_t addr, uint32_t cta) {
  uint32_t r;
  asm volatile("mapa.shared::cluster.u32 %0, %1, %2;" : "=r"(r) : "r"(addr), "r"(cta));
  return r;
}
__device__ __forceinline__ void tma_load(uint32_t dst, const CUtensorMap* tm, int c0, int c1, uint32_t bar) {
  asm volatile("cp.async.bulk.tensor.2d.shared::cluster.global.mbarrier::complete_tx::bytes [%0], [%1, {%3, %4}], [%2];"
               ::"r"(dst), "l"(tm), "r"(bar), "r"(c0), "r"(c1) : "memory");
}
__device__ __forceinline__ void tma_load_mc(uint32_t dst, const CUtensorMap* tm, int c0, int c1, uint32_t bar) {
  asm volatile("cp.async.bulk.tensor.2d.shared::cluster.global.mbarrier::complete_tx::bytes.multicast::cluster [%0], [%1, {%3, %4}], [%2], %5;"
               ::"r"(dst), "l"(tm), "r"(bar), "r"(c0), "r"(c1), "h"((uint16_t)3) : "memory");
}
__device__ __forceinline__ void tma_store(const CUtensorMap* tm, uint32_t src, int c0, int c1) {
  asm volatile("cp.async.bulk.tensor.2d.global.shared::cta.bulk_group [%0, {%2, %3}], [%1];"
               ::"l"(tm), "r"(src), "r"(c0), "r"(c1) : "memory");
}
__device__ __forceinline__ void bulk_commit() { asm volatile("cp.async.bulk.commit_group;" ::: "memory"); }
__device__ __forceinline__ void bulk_wait_read0() { asm volatile("cp.async.bulk.wait_group.read 0;" ::: "memory"); }
__device__ __forceinline__ void bulk_wait0() { asm volatile("cp.async.bulk.wait_group 0;" ::: "memory"); }
__device__ __forceinline__ void fence_async_smem() { asm volatile("fence.proxy.async.shared::cta;" ::: "memory"); }
__device__ __forceinline__ void named_sync(int id, int n) { asm volatile("bar.sync %0, %1;" ::"r"(id), "r"(n) : "memory"); }
__device__ __forceinline__ void named_arrive(int id, int n) { asm volatile("bar.arrive %0, %1;" ::"r"(id), "r"(n) : "memory"); }
__device__ __forceinline__ void cluster_sync() {
  asm volatile("barrier.cluster.arrive.aligned;\nbarrier.cluster.wait.aligned;" ::: "memory");
}
__device__ __forceinline__ void stmatrix_x4(uint32_t addr, uint32_t r0, uint32_t r1, uint32_t r2, uint32_t r3) {
  asm volatile("stmatrix.sync.aligned.m8n8.x4.shared.b16 [%0], {%1, %2, %3, %4};"
               ::"r"(addr), "r"(r0), "r"(r1), "r"(r2), "r"(r3) : "memory");
}
__device__ __forceinline__ uint32_t pack_bf16(float lo, float hi) {
  uint32_t r;
  asm("cvt.rn.bf16x2.f32 %0, %1, %2;" : "=r"(r) : "f"(hi), "f"(lo));
  return r;
}
__device__ __forceinline__ float ex2(float x) {
  float r;
  asm("ex2.approx.ftz.f32 %0, %1;" : "=f"(r) : "f"(x));
  return r;
}
__device__ __forceinline__ float tanh_f(float x) {
  float r;
  asm("tanh.approx.f32 %0, %1;" : "=f"(r) : "f"(x));
  return r;
}
__device__ __forceinline__ void bulk_store(void* dst, uint32_t src, uint32_t bytes) {
  asm volatile("cp.async.bulk.global.shared::cta.bulk_group [%0], [%1], %2;" ::"l"(dst), "r"(src), "r"(bytes) : "memory");
}
__device__ __forceinline__ uint32_t ldg_v(const void* ptr) {
  uint32_t v;
  asm volatile("ld.global.nc.b32 %0, [%1];" : "=r"(v) : "l"(ptr));
  return v;
}
__device__ __forceinline__ float rbf(float x) { return __bfloat162float(__float2bfloat16(x)); }

#define WG_FENCE() asm volatile("wgmma.fence.sync.aligned;" ::: "memory")
#define WG_COMMIT() asm volatile("wgmma.commit_group.sync.aligned;" ::: "memory")
#define WG_WAIT(n) asm volatile("wgmma.wait_group.sync.aligned %0;" ::"n"(n) : "memory")

#define R8(a, o) "+f"(a[o + 0]), "+f"(a[o + 1]), "+f"(a[o + 2]), "+f"(a[o + 3]), "+f"(a[o + 4]), "+f"(a[o + 5]), "+f"(a[o + 6]), "+f"(a[o + 7])
#define R64(a) R8(a, 0), R8(a, 8), R8(a, 16), R8(a, 24), R8(a, 32), R8(a, 40), R8(a, 48), R8(a, 56)
#define L64 "{%0,%1,%2,%3,%4,%5,%6,%7,%8,%9,%10,%11,%12,%13,%14,%15,%16,%17,%18,%19,%20,%21,%22,%23,%24,%25,%26,%27,%28,%29,%30,%31," \
            "%32,%33,%34,%35,%36,%37,%38,%39,%40,%41,%42,%43,%44,%45,%46,%47,%48,%49,%50,%51,%52,%53,%54,%55,%56,%57,%58,%59,%60,%61,%62,%63}"

__device__ __forceinline__ uint64_t make_desc(uint32_t addr, uint32_t lbo) {
  uint64_t d;
  asm("mov.b64 %0, {%1, %2};" : "=l"(d) : "r"((addr >> 4) + ((lbo >> 4) << 16)), "r"(64u | (1u << 30)));
  return d;
}
#define W8(a, o) "=f"(a[o + 0]), "=f"(a[o + 1]), "=f"(a[o + 2]), "=f"(a[o + 3]), "=f"(a[o + 4]), "=f"(a[o + 5]), "=f"(a[o + 6]), "=f"(a[o + 7])
#define W64(a) W8(a, 0), W8(a, 8), W8(a, 16), W8(a, 24), W8(a, 32), W8(a, 40), W8(a, 48), W8(a, 56)
#define R96(a) R64(a), R8(a, 64), R8(a, 72), R8(a, 80), R8(a, 88)
#define L96 "{%0,%1,%2,%3,%4,%5,%6,%7,%8,%9,%10,%11,%12,%13,%14,%15,%16,%17,%18,%19,%20,%21,%22,%23,%24,%25,%26,%27,%28,%29,%30,%31," \
            "%32,%33,%34,%35,%36,%37,%38,%39,%40,%41,%42,%43,%44,%45,%46,%47,%48,%49,%50,%51,%52,%53,%54,%55,%56,%57,%58,%59,%60,%61,%62,%63," \
            "%64,%65,%66,%67,%68,%69,%70,%71,%72,%73,%74,%75,%76,%77,%78,%79,%80,%81,%82,%83,%84,%85,%86,%87,%88,%89,%90,%91,%92,%93,%94,%95}"
template <int TA, int TB, int OA, int OB>
__device__ __forceinline__ void wgmma_ss(float (&d)[64], uint64_t a, uint64_t b) {
  asm volatile("{\n.reg .b64 da, db;\nadd.s64 da, %64, %66;\nadd.s64 db, %65, %67;\n"
               "wgmma.mma_async.sync.aligned.m64n128k16.f32.bf16.bf16 " L64 ", da, db, 1, 1, 1, %68, %69;\n}\n"
               : R64(d) : "l"(a), "l"(b), "n"(OA), "n"(OB), "n"(TA), "n"(TB));
}
template <int TA, int TB>
__device__ __forceinline__ void wgmma_ss_first(float (&d)[64], uint64_t a, uint64_t b) {
  asm volatile("wgmma.mma_async.sync.aligned.m64n128k16.f32.bf16.bf16 " L64 ", %64, %65, 0, 1, 1, %66, %67;\n"
               : W64(d) : "l"(a), "l"(b), "n"(TA), "n"(TB));
}
template <int TA, int TB>
__device__ __forceinline__ void wgmma_ss_p(float (&d)[64], uint64_t a, uint64_t b, int acc) {
  asm volatile("{\n.reg .pred p;\nsetp.ne.b32 p, %66, 0;\n"
               "wgmma.mma_async.sync.aligned.m64n128k16.f32.bf16.bf16 " L64 ", %64, %65, p, 1, 1, %67, %68;\n}\n"
               : R64(d) : "l"(a), "l"(b), "r"(acc), "n"(TA), "n"(TB));
}
template <int TB, int OB>
__device__ __forceinline__ void wgmma_rs(float (&d)[64], const uint32_t* a, uint64_t b) {
  asm volatile("{\n.reg .b64 db;\nadd.s64 db, %68, %69;\n"
               "wgmma.mma_async.sync.aligned.m64n128k16.f32.bf16.bf16 " L64 ", {%64,%65,%66,%67}, db, 1, 1, 1, %70;\n}\n"
               : R64(d) : "r"(a[0]), "r"(a[1]), "r"(a[2]), "r"(a[3]), "l"(b), "n"(OB), "n"(TB));
}
template <int TB>
__device__ __forceinline__ void wgmma_rs_p(float (&d)[64], const uint32_t* a, uint64_t b, int acc) {
  asm volatile("{\n.reg .pred p;\nsetp.ne.b32 p, %69, 0;\n"
               "wgmma.mma_async.sync.aligned.m64n128k16.f32.bf16.bf16 " L64 ", {%64,%65,%66,%67}, %68, p, 1, 1, %70;\n}\n"
               : R64(d) : "r"(a[0]), "r"(a[1]), "r"(a[2]), "r"(a[3]), "l"(b), "r"(acc), "n"(TB));
}
template <int TA, int TB, int OA, int OB>
__device__ __forceinline__ void wgmma_ss192(float (&d)[96], uint64_t a, uint64_t b) {
  asm volatile("{\n.reg .b64 da, db;\nadd.s64 da, %96, %98;\nadd.s64 db, %97, %99;\n"
               "wgmma.mma_async.sync.aligned.m64n192k16.f32.bf16.bf16 " L96 ", da, db, 1, 1, 1, %100, %101;\n}\n"
               : R96(d) : "l"(a), "l"(b), "n"(OA), "n"(OB), "n"(TA), "n"(TB));
}
template <int N>
__device__ __forceinline__ void fence_regs(float (&d)[N]) {
#pragma unroll
  for (int i = 0; i < N; i++) asm volatile("" : "+f"(d[i])::"memory");
}
template <int N>
__device__ __forceinline__ void fence_regs(uint32_t (&d)[N]) {
#pragma unroll
  for (int i = 0; i < N; i++) asm volatile("" : "+r"(d[i])::"memory");
}

__device__ __forceinline__ float half_sum(float v) {
#pragma unroll
  for (int o = 8; o; o >>= 1) v += __shfl_xor_sync(0xffffffffu, v, o);
  return v;
}
__device__ __forceinline__ void ln_rows(uint4 (&u)[5], uint4* gdst, uint32_t sdst, uint32_t bar0) {
#pragma unroll 1
  for (int pass = 0; pass < 2; pass++) {
    float v[40];
    float s = 0.f;
#pragma unroll
    for (int i = 0; i < 5; i++) {
      const uint32_t w[4] = {u[i].x, u[i].y, u[i].z, u[i].w};
#pragma unroll
      for (int q = 0; q < 4; q++) {
        v[8 * i + 2 * q] = __uint_as_float(w[q] << 16);
        v[8 * i + 2 * q + 1] = __uint_as_float(w[q] & 0xffff0000u);
        s += v[8 * i + 2 * q] + v[8 * i + 2 * q + 1];
      }
    }
    const float mean = half_sum(s) * (1.f / DM);
    float q0 = 0.f, q1 = 0.f;
#pragma unroll
    for (int i = 0; i < 20; i++) { float d0 = v[2 * i] - mean, d1 = v[2 * i + 1] - mean; q0 += d0 * d0; q1 += d1 * d1; }
    const float var = half_sum(q0 + q1) * (1.f / DM);
    const float m = rbf(mean);
    float den;
    asm("sqrt.approx.f32 %0, %1;" : "=f"(den) : "f"(rbf(rbf(var) + 1e-5f)));
    const float inv = __fdividef(1.f, rbf(den));
#pragma unroll
    for (int i = 0; i < 5; i++) {
      uint32_t w[4];
#pragma unroll
      for (int q = 0; q < 4; q++) {
        uint32_t c = pack_bf16(v[8 * i + 2 * q] - m, v[8 * i + 2 * q + 1] - m);
        w[q] = pack_bf16(__uint_as_float(c << 16) * inv, __uint_as_float(c & 0xffff0000u) * inv);
      }
      u[i] = make_uint4(w[0], w[1], w[2], w[3]);
      if (pass == 0) gdst[i * 16] = u[i];
      else asm volatile("st.shared.v4.b32 [%0], {%1,%2,%3,%4};" ::"r"(sdst + i * 256), "r"(w[0]), "r"(w[1]), "r"(w[2]), "r"(w[3]) : "memory");
    }
    if (pass) fence_async_smem();
    __syncwarp();
    if ((threadIdx.x & 31) == 0) mbar_arrive_local(bar0 + pass * 8);
    __syncwarp();
  }
}

constexpr int NA = NSTAGE, NG = NSTAGE + 1;
struct Pipe {
  uint32_t stage, lap, ph5;
  template <int N> __device__ __forceinline__ uint32_t phase() const { return (N == NG && stage == NA) ? ph5 : lap; }
  template <int N> __device__ __forceinline__ void next() {
    if (++stage == N) { stage = 0; lap ^= 1; if (N == NG) ph5 ^= 1; }
  }
  __device__ __forceinline__ void enter_attn() { if (stage == NA) { stage = 0; lap ^= 1; } }
};

enum { IT_NONE = 0, IT_ATTN1 = 1, IT_ATTN2 = 2, IT_M1 = 3, IT_M2 = 4, IT_OP = 5 };

__device__ __forceinline__ void release_stage(uint32_t empty_mapped, uint32_t stage, int lane) {
  asm volatile("{\n.reg .pred p;\nsetp.lt.s32 p, %1, 2;\n@p mbarrier.arrive.shared::cluster.b64 _, [%0];\n}\n"
               ::"r"(empty_mapped + stage * 8), "r"(lane) : "memory");
}
__device__ __forceinline__ void release_stage2(uint32_t empty_mapped, uint32_t stage, int lane) {
  asm volatile("{\n.reg .pred p;\nsetp.lt.s32 p, %1, 2;\n@p mbarrier.arrive.shared::cluster.b64 _, [%0], 2;\n}\n"
               ::"r"(empty_mapped + stage * 8), "r"(lane) : "memory");
}
__device__ __forceinline__ void warp_arrive(uint32_t bar, int lane_sel) {
  __syncwarp();
  asm volatile("{\n.reg .pred p;\nsetp.eq.s32 p, %1, 0;\n@p mbarrier.arrive.shared::cta.b64 _, [%0];\n}\n"
               ::"r"(bar), "r"(lane_sel) : "memory");
}

template <int TA, bool ZEROED>
__device__ __forceinline__ void mma_k64(float (&acc)[64], uint64_t a, uint64_t b, int accum) {
  constexpr int SA = TA ? 128 : 2;
  if (ZEROED) wgmma_ss<TA, 1, 0, 0>(acc, a, b); else wgmma_ss_p<TA, 1>(acc, a, b, accum);
  wgmma_ss<TA, 1, SA, 128>(acc, a, b);
  wgmma_ss<TA, 1, 2 * SA, 256>(acc, a, b);
  wgmma_ss<TA, 1, 3 * SA, 384>(acc, a, b);
}
template <int TA, bool ZEROED>
__device__ __forceinline__ void gemm_kstep(float (&acc)[64], uint32_t sb, int wg, int accum) {
  mma_k64<TA, ZEROED>(acc, make_desc(sb + wg * 8192, TA ? 8192 : 16), make_desc(sb + 16384, 8192), accum);
}

template <int TA, int NR, bool DRAIN>
__device__ __forceinline__ void gemm_loop(float (&acc)[64], int ks0, int ksteps, uint32_t& prev, Pipe& pp, uint32_t sbase,
                                          uint32_t full0, uint32_t empty_mapped, int wg, int lane) {
#pragma unroll 1
  for (int ks = ks0; ks < ksteps; ks++) {
    mbar_wait(full0 + pp.stage * 8, pp.template phase<NR>());
    WG_FENCE();
    gemm_kstep<TA, true>(acc, sbase + pp.stage * STAGE_BYTES, wg, 1);
    WG_COMMIT();
    WG_WAIT(1);
    release_stage(empty_mapped, prev, ks > 0 ? lane : 32);
    prev = pp.stage;
    pp.template next<NR>();
  }
  if (DRAIN) {
    WG_WAIT(0);
    fence_regs(acc);
    release_stage(empty_mapped, prev, lane);
  }
}

__device__ __forceinline__ void stage_tile(const uint32_t (&r)[32], uint32_t buf, int warp_in_wg, int lane) {
  int mi = lane >> 3;
  int row = warp_in_wg * 16 + (mi & 1) * 8 + (lane & 7);
  uint32_t rowaddr = buf + row * 128;
#pragma unroll
  for (int kk = 0; kk < 8; kk++) {
    int chunk = ((2 * kk) & 7) + (mi >> 1);
    uint32_t addr = rowaddr + (kk >> 2) * 8192 + ((chunk ^ (lane & 7)) << 4);
    stmatrix_x4(addr, r[4 * kk], r[4 * kk + 1], r[4 * kk + 2], r[4 * kk + 3]);
  }
}

constexpr float LOG2E = 1.4426950408889634f;
constexpr float SCALE_LOG2E = 0.08838834764831845f * LOG2E;

__device__ __forceinline__ float quad_max(float v) {
  v = fmaxf(v, __shfl_xor_sync(0xffffffffu, v, 1));
  return fmaxf(v, __shfl_xor_sync(0xffffffffu, v, 2));
}
__device__ __forceinline__ float quad_sum(float v) {
  v += __shfl_xor_sync(0xffffffffu, v, 1);
  return v + __shfl_xor_sync(0xffffffffu, v, 2);
}

__device__ __forceinline__ void exp_block(const float (&S)[64], uint32_t (&P)[32], float& bs0, float& bs1) {
  float a0 = 0.f, a1 = 0.f, c0 = 0.f, c1 = 0.f;
#pragma unroll
  for (int i = 0; i < 16; i++) {
    float p0 = ex2(S[4 * i + 0]), p1 = ex2(S[4 * i + 1]), p2 = ex2(S[4 * i + 2]), p3 = ex2(S[4 * i + 3]);
    if (i == 0) { a0 = p0; c0 = p1; a1 = p2; c1 = p3; }
    else { a0 += p0; c0 += p1; a1 += p2; c1 += p3; }
    P[2 * i] = pack_bf16(p0, p1);
    P[2 * i + 1] = pack_bf16(p2, p3);
  }
  bs0 = a0 + c0; bs1 = a1 + c1;
}
__device__ __forceinline__ void row_max(const float (&S)[64], float& x0, float& x1) {
  float a0 = fmaxf(S[0], S[1]), a1 = fmaxf(S[2], S[3]);
#pragma unroll
  for (int i = 1; i < 16; i++) {
    a0 = fmaxf(a0, fmaxf(S[4 * i], S[4 * i + 1]));
    a1 = fmaxf(a1, fmaxf(S[4 * i + 2], S[4 * i + 3]));
  }
  x0 = quad_max(a0); x1 = quad_max(a1);
}

struct SmState { float m0, m1, l0, l1; bool sub; };
constexpr float BS_HI = 1099511627776.f;
constexpr float BS_LO = 5.9604644775390625e-8f;

__device__ __forceinline__ void issue_qk(float (&S)[64], uint64_t q, uint64_t k) {
  wgmma_ss_first<0, 0>(S, q, k);
  wgmma_ss<0, 0, 2, 2>(S, q, k); wgmma_ss<0, 0, 4, 4>(S, q, k); wgmma_ss<0, 0, 6, 6>(S, q, k);
  wgmma_ss<0, 0, 512, 1024>(S, q, k); wgmma_ss<0, 0, 514, 1026>(S, q, k); wgmma_ss<0, 0, 516, 1028>(S, q, k); wgmma_ss<0, 0, 518, 1030>(S, q, k);
}
__device__ __forceinline__ void issue_pv(float (&O)[64], const uint32_t (&P)[32], uint64_t v, int acc, int other) {
  wgmma_rs_p<1>(O, &P[0], v, acc);
  wgmma_rs<1, 128>(O, &P[4], v); wgmma_rs<1, 256>(O, &P[8], v); wgmma_rs<1, 384>(O, &P[12], v);
  wgmma_rs<1, 512>(O, &P[16], v); wgmma_rs<1, 640>(O, &P[20], v);
  named_arrive(other, 256);
  wgmma_rs<1, 768>(O, &P[24], v); wgmma_rs<1, 896>(O, &P[28], v);
}

__device__ __forceinline__ bool softmax_block(float (&S)[64], uint32_t (&P)[32], SmState& st, bool first, float& f0, float& f1) {
  float d0 = st.m0, d1 = st.m1, bs0, bs1;
  const float lo = first ? BS_LO : 0.f;
  bool resc = false;
#pragma unroll 1
  for (int pass = 0;; pass++) {
    if (st.sub) {
#pragma unroll
      for (int i = 0; i < 16; i++) { S[4 * i] -= d0; S[4 * i + 1] -= d0; S[4 * i + 2] -= d1; S[4 * i + 3] -= d1; }
    }
    exp_block(S, P, bs0, bs1);
    if (!__any_sync(0xffffffffu, !(fmaxf(bs0, bs1) <= BS_HI && fminf(bs0, bs1) >= lo)) || pass) break;
    row_max(S, d0, d1);
    if (!first) { d0 = fmaxf(d0, 0.f); d1 = fmaxf(d1, 0.f); }
    if (d0 == -INFINITY) d0 = 0.f;
    if (d1 == -INFINITY) d1 = 0.f;
    st.m0 += d0; st.m1 += d1; st.sub = true;
    if (!first) {
      f0 = ex2(-d0); f1 = ex2(-d1);
      st.l0 *= f0; st.l1 *= f1;
      resc = true;
    }
  }
  st.l0 += bs0; st.l1 += bs1;
  return resc;
}
__device__ __forceinline__ void pack_scaled(const float (&A)[64], uint32_t (&R)[32], float s0, float s1) {
#pragma unroll
  for (int i = 0; i < 16; i++) {
    R[2 * i] = pack_bf16(A[4 * i] * s0, A[4 * i + 1] * s0);
    R[2 * i + 1] = pack_bf16(A[4 * i + 2] * s1, A[4 * i + 3] * s1);
  }
}

template <bool ODD>
__device__ __forceinline__ void attn_step(float (&S)[64], float (&O)[64], uint32_t (&Pc)[32], uint32_t (&Pn)[32],
                                          uint32_t qaddr, SmState& st, int acc, Pipe& pp, uint32_t sbase,
                                          uint32_t full0, uint32_t empty_mapped, int wg, int lane,
                                          bool special, uint32_t obuf, uint32_t obar) {
  uint32_t ks = pp.stage;
  mbar_wait(full0 + pp.stage * 8, pp.phase<NA>());
  pp.next<NA>();
  uint32_t vs = pp.stage;
  mbar_wait(full0 + pp.stage * 8, pp.phase<NA>());
  pp.next<NA>();
  named_sync(1 + wg, 256);
  WG_FENCE();
  issue_qk(S, make_desc(qaddr, 16), make_desc(sbase + ks * STAGE_BYTES, 16));
  WG_COMMIT();
  float f0 = 1.f, f1 = 1.f;
  if (special) {
    if (!ODD) {
      stage_tile(Pn, obuf, (threadIdx.x >> 5) & 3, lane);
      fence_async_smem();
      warp_arrive(obar, obar ? lane : 1);
    } else {
      f0 = __fdividef(1.f, quad_sum(st.l0)); f1 = __fdividef(1.f, quad_sum(st.l1));
      st.m0 = st.m1 = st.l0 = st.l1 = 0.f; st.sub = false;
    }
  }
  WG_FENCE();
  issue_pv(O, Pc, make_desc(sbase + vs * STAGE_BYTES, 16384), acc, 2 - wg);
  WG_COMMIT();
  WG_WAIT(1);
  fence_regs(S);
  release_stage(empty_mapped, ks, lane);
  const bool resc = softmax_block(S, Pn, st, ODD && special, f0, f1);
  WG_WAIT(0);
  fence_regs(O);
  fence_regs(Pc);
  release_stage(empty_mapped, vs, lane);
  if (resc) {
#pragma unroll
    for (int i = 0; i < 16; i++) { O[4 * i] *= f0; O[4 * i + 1] *= f0; O[4 * i + 2] *= f1; O[4 * i + 3] *= f1; }
  }
  if (ODD && special) pack_scaled(O, Pc, f0, f1);
}

__device__ __forceinline__ float silu_f(float v) {
  float h = 0.5f * v;
  return fmaf(h, tanh_f(h), h);
}
__device__ __forceinline__ float gelu_f(float v) {
  float z = v * fmaf(v * v, 0.044715f * 0.7978845608028654f, 0.7978845608028654f);
  float h = 0.5f * v;
  return fmaf(h, tanh_f(z), h);
}

template <int N>
__device__ __forceinline__ void gelu_inplace(uint32_t addr) {
  uint32_t v[4 * N];
#pragma unroll
  for (int c = 0; c < N; c++)
    asm volatile("ld.shared.v4.b32 {%0,%1,%2,%3}, [%4];" : "=r"(v[4 * c]), "=r"(v[4 * c + 1]), "=r"(v[4 * c + 2]), "=r"(v[4 * c + 3]) : "r"(addr + c * 512) : "memory");
#pragma unroll
  for (int i = 0; i < 4 * N; i++) v[i] = pack_bf16(gelu_f(__uint_as_float(v[i] << 16)), gelu_f(__uint_as_float(v[i] & 0xffff0000u)));
#pragma unroll
  for (int c = 0; c < N; c++)
    asm volatile("st.shared.v4.b32 [%0], {%1,%2,%3,%4};" ::"r"(addr + c * 512), "r"(v[4 * c]), "r"(v[4 * c + 1]), "r"(v[4 * c + 2]), "r"(v[4 * c + 3]) : "memory");
}
__device__ __forceinline__ void qp_group(float (&acc)[64], uint32_t xaddr, uint32_t waddr, uint32_t wlbo) {
  mma_k64<0, true>(acc, make_desc(xaddr, 16), make_desc(waddr, wlbo), 1);
}

#define STAGGER 1
#define PREFETCH 3
#define PF_LATE 105000
#define M1_FIRST 0
#define NY 7
#define KG0 55
#define PFD 4
#define G_EARLY 0

__global__ void __cluster_dims__(2, 1, 1) __launch_bounds__(384, 1) mega_kernel(const __grid_constant__ Params p) {
  extern __shared__ uint8_t smem_raw[];
  const uint32_t sbase = (smem_u32(smem_raw) + 1023) & ~1023u;
  const uint32_t full0 = sbase + BAR_OFF;
  const uint32_t empty0 = full0 + 64;
  const uint32_t stq0 = full0 + 128;
  const uint32_t stf0 = full0 + 144;
  const uint32_t lnb0 = full0 + 176;
  const uint32_t qfree = full0 + 192;
  const uint32_t ybar = full0 + 200;
  volatile unsigned* epoch_s = reinterpret_cast<volatile unsigned*>(smem_raw + (sbase - smem_u32(smem_raw)) + BAR_OFF + 224);
  volatile unsigned* keep_s = epoch_s + 2;
  const int tid = threadIdx.x;
  const int wg = __shfl_sync(0xffffffffu, tid >> 7, 0);
  const int lane = tid & 31;
  uint32_t rank;
  asm volatile("mov.u32 %0, %%cluster_ctarank;" : "=r"(rank));
  const int cluster_id = blockIdx.x >> 1;
  const uint16_t* items = p.items + cluster_id * MAXITEMS;

  uint4 xr[5];
  const bool ln_cta = blockIdx.x < 128;
  if (wg < 2 && ln_cta) {
    const uint4* src = reinterpret_cast<const uint4*>(p.x + (size_t)(blockIdx.x * 16 + (tid >> 4)) * DM);
#pragma unroll
    for (int i = 0; i < 5; i++) xr[i] = __ldg(src + (lane & 15) + i * 16);
  }
  if (tid == 256) {
    for (int i = 0; i < NSTAGE + 1; i++) { mbar_init(full0 + i * 8, 1); mbar_init(empty0 + i * 8, 16); }
    for (int i = 0; i < 2; i++) { mbar_init(stq0 + i * 8, 4); mbar_init(lnb0 + i * 8, 8); }
    for (int i = 0; i < 4; i++) mbar_init(stf0 + i * 8, 1);
    mbar_init(qfree, 16);
    mbar_init(ybar, 1); mbar_init(ybar + 8, 1);
    asm volatile("fence.mbarrier_init.release.cluster;" ::: "memory");
  }
  __syncthreads();
  asm volatile("barrier.cluster.arrive.relaxed.aligned;" ::: "memory");

  if (wg < 2) {
    asm volatile("setmaxnreg.inc.sync.aligned.u32 240;");
    if (ln_cta)
      ln_rows(xr, reinterpret_cast<uint4*>(g_xn + (size_t)(blockIdx.x * 16 + (tid >> 4)) * DM) + (lane & 15),
              sbase + QB0_OFF + (tid >> 4) * (DM * 2) + (lane & 15) * 16, lnb0);
    asm volatile("barrier.cluster.wait.aligned;" ::: "memory");
    Pipe pp; pp.stage = 0; pp.lap = 0; pp.ph5 = 0;
    const uint32_t empty_mapped = mapa(empty0, lane & 1);
    const uint32_t dbase = sbase & 0x3FFFF;
    const int warp_in_wg = (tid >> 5) & 3;
    const uint32_t qbuf = sbase + QB0_OFF + wg * 16384;
    const int r0 = warp_in_wg * 16 + (lane >> 2);
    const uint32_t stf = stf0 + wg * 16;
    uint32_t stf_ph0 = 0;
    if (wg == 1) named_arrive(1, 256);
    int tls = 0; (void)tls;

#pragma unroll 1
    for (int ii = 0; ii < MAXITEMS; ii++) {
      const uint32_t it = __shfl_sync(0xffffffffu, (uint32_t)items[ii], 0);
      const int type = it >> 13, a = (it >> 10) & 7, b = (it >> 5) & 31;
      TL(tls); tls++;
      if (ii == 1) FT(3);
      if (type == IT_NONE) break;
      const int mrow = (a * 2 + rank) * 128 + wg * 64;
      if (type <= IT_ATTN2) pp.enter_attn();
      if (type == IT_M2) {
        float S[64], T[96];
#pragma unroll
        for (int i = 0; i < 64; i++) S[i] = 0.f;
#pragma unroll
        for (int i = 0; i < 96; i++) T[i] = 0.f;
        uint32_t br0 = __ldg(reinterpret_cast<const unsigned short*>(p.b2) + mrow + r0);
        uint32_t br1 = __ldg(reinterpret_cast<const unsigned short*>(p.b2) + mrow + r0 + 8);
        uint32_t prev = 0, keep = 0;
#pragma unroll 1
        for (int ks = 2 * NY; ks < FF / 32; ks++) {
          mbar_wait(full0 + pp.stage * 8, pp.phase<NG>());
          const uint32_t sb = dbase + pp.stage * STAGE_BYTES;
          const uint64_t da = make_desc(sb + wg * 4096, 4096), db = make_desc(sb + 8192, 4096);
          WG_FENCE();
          wgmma_ss<1, 1, 0, 0>(S, da, db);
          wgmma_ss192<1, 1, 0, 512>(T, da, db);
          wgmma_ss<1, 1, 128, 128>(S, da, db);
          wgmma_ss192<1, 1, 128, 640>(T, da, db);
          WG_COMMIT();
          WG_WAIT(1);
          release_stage(empty_mapped, prev, (ks > 2 * NY && (ks < FF / 32 - 1 || wg == 1)) ? lane : 32);
          if (ks == FF / 32 - 2 + wg) keep = pp.stage;
          prev = pp.stage;
          pp.next<NG>();
        }
        WG_WAIT(0);
        fence_regs(S);
        fence_regs(T);
        release_stage(empty_mapped, prev, wg == 0 ? lane : 32);
        TL(tls); tls++;
        asm volatile("" : "+r"(br0), "+r"(br1));
        const float bb0 = __uint_as_float(br0 << 16), bb1 = __uint_as_float(br1 << 16);
        if ((tid & 127) == 0) keep_s[wg] = keep;
        named_sync(5, 256);
        mbar_wait(stf, stf_ph0);
#pragma unroll
        for (int c = 0; c < 20; c++) {
          const float* v = c < 8 ? &S[8 * c] : &T[8 * (c - 8)];
          const uint32_t dst = (c < 16 ? sbase + keep * STAGE_BYTES + warp_in_wg * 8192 + c * 512 : qbuf + warp_in_wg * 2048 + (c - 16) * 512) + lane * 16;
          asm volatile("st.shared.v4.b32 [%0], {%1,%2,%3,%4};" ::"r"(dst), "r"(pack_bf16(v[0] + bb0, v[1] + bb0)), "r"(pack_bf16(v[2] + bb1, v[3] + bb1)),
                       "r"(pack_bf16(v[4] + bb0, v[5] + bb0)), "r"(pack_bf16(v[6] + bb1, v[7] + bb1)) : "memory");
        }
        fence_async_smem();
        warp_arrive(stq0 + wg * 8, lane);
        stf_ph0 ^= 1;
      } else if (type == IT_OP) {
        float S[64], Y[64];
#pragma unroll
        for (int i = 0; i < 64; i++) { S[i] = 0.f; Y[i] = 0.f; }
        uint32_t X[32], G[32];
        uint32_t prev = 0;
        gemm_loop<1, NG, false>(Y, 0, NY, prev, pp, dbase, full0, empty_mapped, wg, lane);
        gemm_loop<0, NG, false>(S, 1, 5 + wg * 4, prev, pp, dbase, full0, empty_mapped, wg, lane);
        TL(tls); tls++;
        {
          const bf16* x0 = p.x + (size_t)(mrow + r0) * DM + b * 128 + (lane & 3) * 2;
#pragma unroll
          for (int i = 0; i < 16; i++) { X[2 * i] = ldg_v(x0 + i * 8); X[2 * i + 1] = ldg_v(x0 + 8 * DM + i * 8); }
        }
        const int kg = KG0 + wg * 4;
        gemm_loop<0, NG, false>(S, 5 + wg * 4, kg + 1, prev, pp, dbase, full0, empty_mapped, wg, lane);
        fence_regs(Y);
        TL(tls); tls++;
        mbar_wait(ybar + wg * 8, 0);
        TL(tls); tls++;
#pragma unroll
        for (int q = 0; q < 4; q++) {
          mbar_wait(full0 + pp.stage * 8, pp.phase<NG>());
          WG_FENCE();
          gemm_kstep<0, true>(S, dbase + pp.stage * STAGE_BYTES, wg, 1);
          WG_COMMIT();
#pragma unroll
          for (int c = 2 * q; c < 2 * q + 2; c++)
            asm volatile("ld.shared.v4.b32 {%0,%1,%2,%3}, [%4];" : "=r"(G[4 * c]), "=r"(G[4 * c + 1]), "=r"(G[4 * c + 2]), "=r"(G[4 * c + 3])
                         : "r"(qbuf + warp_in_wg * 4096 + c * 512 + lane * 16) : "memory");
#pragma unroll
          for (int i = 8 * q; i < 8 * q + 8; i++) {
            G[i] = pack_bf16(silu_f(Y[2 * i] + __uint_as_float(G[i] << 16)), silu_f(Y[2 * i + 1] + __uint_as_float(G[i] & 0xffff0000u)));
            asm volatile("" : "+r"(G[i]));
          }
          WG_WAIT(1);
          release_stage(empty_mapped, prev, lane);
          prev = pp.stage;
          pp.next<NG>();
        }
        named_sync(3 + wg, 128);
        TL(tls); tls++;
        gemm_loop<0, NG, true>(S, kg + 5, HD / 64 + 1, prev, pp, dbase, full0, empty_mapped, wg, lane);
        TL(tls); tls++;
#pragma unroll
        for (int i = 0; i < 32; i++) {
          float v0 = fmaf(S[2 * i], __uint_as_float(G[i] << 16), __uint_as_float(X[i] << 16));
          float v1 = fmaf(S[2 * i + 1], __uint_as_float(G[i] & 0xffff0000u), __uint_as_float(X[i] & 0xffff0000u));
          X[i] = pack_bf16(v0, v1);
        }
        stage_tile(X, qbuf, warp_in_wg, lane);
        fence_async_smem();
        warp_arrive(stq0 + wg * 8, lane);
        stf_ph0 ^= 1;
      } else if (type == IT_M1) {
        const uint32_t stage0 = sbase + QB0_OFF;
        const uint32_t el = stage0 + warp_in_wg * 2048 + lane * 16;
        uint32_t cur = it;
#pragma unroll 1
        for (int n = 0;; n++) {
          const uint32_t nx = __shfl_sync(0xffffffffu, (uint32_t)items[ii + 1], 0);
          const bool last = (nx >> 13) != IT_M1;
          if ((n & 1) == wg) {
            float S[64], T[64];
#pragma unroll
            for (int i = 0; i < 64; i++) { S[i] = 0.f; T[i] = 0.f; }
            const int row = (((cur >> 10) & 7) * 2 + rank) * 128 + r0;
            uint32_t br[4];
#pragma unroll
            for (int q = 0; q < 4; q++) br[q] = __ldg(reinterpret_cast<const unsigned short*>(p.b1) + min(row + (q & 1) * 8 + (q >> 1) * 64, FF - 1));
            uint32_t prev = 0;
            named_sync(1 + wg, 256);
#pragma unroll 1
            for (int ks = 0; ks < SEQ / 64; ks++) {
              mbar_wait(full0 + pp.stage * 8, pp.phase<NG>());
              const uint32_t sb = dbase + pp.stage * STAGE_BYTES;
              const uint64_t da = make_desc(sb, 8192), db = make_desc(sb + 16384, 8192);
              WG_FENCE();
              wgmma_ss<1, 1, 0, 0>(S, da, db);     wgmma_ss<1, 1, 512, 0>(T, da, db);
              wgmma_ss<1, 1, 128, 128>(S, da, db); wgmma_ss<1, 1, 640, 128>(T, da, db);
              wgmma_ss<1, 1, 256, 256>(S, da, db); wgmma_ss<1, 1, 768, 256>(T, da, db);
              wgmma_ss<1, 1, 384, 384>(S, da, db); wgmma_ss<1, 1, 896, 384>(T, da, db);
              WG_COMMIT();
              WG_WAIT(1);
              release_stage2(empty_mapped, prev, ks > 0 ? lane : 32);
              prev = pp.stage;
              pp.next<NG>();
            }
            named_arrive(2 - wg, 256);
            WG_WAIT(0);
            fence_regs(S);
            fence_regs(T);
            release_stage2(empty_mapped, prev, lane);
            fence_regs(br);
            uint32_t U[32];
#pragma unroll
            for (int i = 0; i < 32; i++) { const float bb = __uint_as_float(br[i & 1] << 16); U[i] = pack_bf16(S[2 * i] + bb, S[2 * i + 1] + bb); }
            mbar_wait(stf0, stf_ph0);
            stage_tile(U, stage0, warp_in_wg, lane);
#pragma unroll
            for (int i = 0; i < 32; i++) { const float bb = __uint_as_float(br[2 + (i & 1)] << 16); U[i] = pack_bf16(T[2 * i] + bb, T[2 * i + 1] + bb); }
            mbar_wait(stf0 + 16, stf_ph0);
            stage_tile(U, stage0 + 16384, warp_in_wg, lane);
            __syncwarp();
            if (!last) {
              const uint32_t ew = stage0 + warp_in_wg * 2048 + lane * 4;
#pragma unroll 1
              for (int k = 0; k < 64; k++) {
                const uint32_t ad = ew + (k >> 4) * 8192 + (k & 15) * 128;
                uint32_t v;
                asm volatile("ld.shared.b32 %0, [%1];" : "=r"(v) : "r"(ad) : "memory");
                v = pack_bf16(gelu_f(__uint_as_float(v << 16)), gelu_f(__uint_as_float(v & 0xffff0000u)));
                asm volatile("st.shared.b32 [%0], %1;" ::"r"(ad), "r"(v) : "memory");
              }
              fence_async_smem();
              warp_arrive(stq0, lane);
              warp_arrive(stq0 + 8, lane);
            }
          } else {
            pp.lap ^= 1; pp.ph5 ^= 1;
            pp.next<NG>(); pp.next<NG>();
            if (last && wg == 1) { named_sync(2, 256); named_arrive(1, 256); }
          }
          TL(tls); tls++;
          stf_ph0 ^= 1;
          if (last) break;
          ii++;
          cur = nx;
        }
        named_sync(5, 256);
#pragma unroll 1
        for (int k = 0; k < 4; k++) gelu_inplace<2>(el + wg * 16384 + (k >> 1) * 8192 + (k & 1) * 1024);
        fence_async_smem();
        warp_arrive(stq0 + wg * 8, lane);
      } else {
        uint32_t P0[32], P1[32];
        SmState st;
        uint32_t qaddr = dbase + QB0_OFF + wg * 16384;
        if (__builtin_expect(type == IT_ATTN1, 0)) {
          float S[64];
#pragma unroll
          for (int i = 0; i < 64; i++) S[i] = 0.f;
          uint32_t prev = 0;
          gemm_loop<0, NA, true>(S, 0, DM / 64, prev, pp, dbase, full0, empty_mapped, wg, lane);
          TL(tls);
          pack_scaled(S, P1, SCALE_LOG2E, SCALE_LOG2E);
          mbar_wait(stf, stf_ph0);
          stage_tile(P1, qbuf, warp_in_wg, lane);
          fence_async_smem();
        } else {
          float S[64], O[64];
#pragma unroll
          for (int i = 0; i < 64; i++) { S[i] = 0.f; O[i] = 0.f; }
          uint32_t sc = 0;
#pragma unroll 1
          for (int m = 0; m < 5; m++) {
            const uint32_t sa = pp.stage;
            mbar_wait(full0 + pp.stage * 8, pp.phase<NA>()); pp.next<NA>();
            const uint32_t xa = dbase + sa * STAGE_BYTES;
            if (ii == 1 && m == 0) FT(4);
            if (ii == 1 && m == 1) FT(5);
            if (ii == 1 && m == 4) FT(6);
            if (STAGGER && m == 4) named_sync(1 + wg, 256);
            if (ii == 1 && m == 4) FT(7);
            WG_FENCE();
            qp_group(O, xa + wg * 8192, xa + 16384, 8192);
            WG_COMMIT();
            WG_WAIT(1);
            release_stage(empty_mapped, sc, m > 0 ? lane : 32);
            const uint32_t sb = pp.stage;
            mbar_wait(full0 + pp.stage * 8, pp.phase<NA>()); pp.next<NA>();
            const uint32_t xb = dbase + sb * STAGE_BYTES;
            WG_FENCE();
            qp_group(S, xa + wg * 8192, xb, 16384);
            WG_COMMIT();
            sc = pp.stage;
            mbar_wait(full0 + pp.stage * 8, pp.phase<NA>()); pp.next<NA>();
            const uint32_t xc = dbase + sc * STAGE_BYTES;
            WG_FENCE();
            qp_group(S, xc + wg * 8192, xb + 8192, 16384);
            WG_COMMIT();
            WG_WAIT(1);
            release_stage(empty_mapped, sa, lane);
            WG_FENCE();
            qp_group(O, xc + wg * 8192, xc + 16384, 8192);
            WG_COMMIT();
            if (STAGGER && m == 4) named_arrive(2 - wg, 256);
            WG_WAIT(1);
            release_stage(empty_mapped, sb, lane);
          }
          fence_regs(S);
          TL(tls);
          if (ii == 1) FT(8);
          pack_scaled(S, P0, SCALE_LOG2E, SCALE_LOG2E);
          mbar_wait(stf, stf_ph0);
          stage_tile(P0, qbuf, warp_in_wg, lane);
          fence_async_smem();
          if (ii == 1) FT(9);
          WG_WAIT(0);
          fence_regs(O);
          release_stage(empty_mapped, sc, lane);
          pack_scaled(O, P1, SCALE_LOG2E, SCALE_LOG2E);
        }
        float S[64], O[64];
        {
          if (ii == 1) FT(10);
          named_sync(3 + wg, 128);
          const uint32_t ks = pp.stage;
          mbar_wait(full0 + pp.stage * 8, pp.phase<NA>()); pp.next<NA>();
          if (ii == 1) FT(11);
          named_sync(1 + wg, 256);
          if (ii == 1) FT(12);
          WG_FENCE();
          issue_qk(S, make_desc(qaddr, 16), make_desc(dbase + ks * STAGE_BYTES, 16));
          WG_COMMIT();
          named_arrive(2 - wg, 256);
#pragma unroll
          for (int i = 0; i < 64; i++) O[i] = 0.f;
          WG_WAIT(0);
          fence_regs(S);
          release_stage(empty_mapped, ks, lane);
        }
        tls++;
        if (ii == 1) FT(13);
        {
          float f0, f1;
          st.m0 = st.m1 = st.l0 = st.l1 = 0.f; st.sub = false;
          softmax_block(S, P0, st, true, f0, f1);
        }
        TL(tls); tls++;
        if (ii == 1) FT(14);
        const int npair = type == IT_ATTN2 ? 16 : 8;
#pragma unroll 1
        for (int j = 0;; j++) {
          attn_step<false>(S, O, P0, P1, qaddr, st, j & 7, pp, dbase, full0, empty_mapped, wg, lane, (j & 7) == 0,
                           j ? qbuf : qbuf - STAGE_BYTES, j ? stq0 + wg * 8 : 0);
          if (ii == 1 && j < 2) FT(15 + 2 * j);
          if (ii == 1 && j >= 6 && j < 10) FT(19 + 2 * (j - 6));
          if ((j & 7) == 7) { TL(tls); tls++; }
          if (j == npair - 1) break;
          if (j == 7) { qaddr -= STAGE_BYTES; stf_ph0 ^= 1; }
          attn_step<true>(S, O, P1, P0, qaddr, st, 1, pp, dbase, full0, empty_mapped, wg, lane, j == 7, 0, 0);
          if (ii == 1 && j < 2) FT(16 + 2 * j);
          if (ii == 1 && j >= 6 && j < 10) FT(20 + 2 * (j - 6));
          if (j == 7) { TL(tls); tls++; }
        }
        {
          release_stage(empty_mapped, (qfree - empty0) >> 3, lane);
          const uint32_t vs = pp.stage;
          mbar_wait(full0 + pp.stage * 8, pp.phase<NA>()); pp.next<NA>();
          if (ii == 0) FT(0);
          named_sync(1 + wg, 256);
          if (ii == 0) FT(1);
          WG_FENCE();
          issue_pv(O, P1, make_desc(dbase + vs * STAGE_BYTES, 16384), 1, 2 - wg);
          WG_COMMIT();
          const float i0 = __fdividef(1.f, quad_sum(st.l0)), i1 = __fdividef(1.f, quad_sum(st.l1));
          WG_WAIT(0);
          fence_regs(O);
          fence_regs(P1);
          release_stage(empty_mapped, vs, lane);
          if (ii == 0) FT(2);
          pack_scaled(O, P0, i0, i1);
          mbar_wait(stf, stf_ph0);
          stage_tile(P0, qbuf, warp_in_wg, lane);
          fence_async_smem();
          warp_arrive(stq0 + wg * 8, lane);
          stf_ph0 ^= 1;
        }
      }
    }
    if (wg == 0) named_sync(1, 256);
  } else {
    asm volatile("setmaxnreg.dec.sync.aligned.u32 24;");
    const int pw = __shfl_sync(0xffffffffu, (tid >> 5) & 3, 0);
    if (pw == 0) {
      unsigned ep = 0;
      if (lane == 0) ep = atomicAdd(&g_epoch[blockIdx.x * 8], 1u) + 1;
      if (lane == 0) *epoch_s = ep;
      ep = __shfl_sync(0xffffffffu, ep, 0);
      asm volatile("barrier.cluster.wait.aligned;" ::: "memory");
      Pipe pp; pp.stage = 0; pp.lap = 1; pp.ph5 = 1;
      uint32_t qf_ph = 1;
      uint32_t ln_ok = 0;
      const unsigned* ln_ptr = &g_cnt_ln[lane * 32];
      if (lane == 0) { TLX(0, 58); }
#pragma unroll 1
      for (int ii = 0; ii < MAXITEMS; ii++) {
        const uint32_t it = __shfl_sync(0xffffffffu, (uint32_t)items[ii], 0);
        const int type = it >> 13, a = (it >> 10) & 7, b = (it >> 5) & 31, c = it & 31;
        if (type == IT_NONE) break;
        const int arow = (a * 2 + rank) * 128;
        if (type <= IT_ATTN2) pp.enter_attn();
        if (type == IT_M2) {
          uint32_t u_ok = 0;
#pragma unroll 1
          for (int ks = 2 * NY; ks < FF / 32; ks++) {
            u_ok = mask_wait(u_ok, 1u << (ks >> 3), 127u, &g_cnt_u[(lane < 7 ? lane : 0) * 32], ep * 20);
            if (pp.stage == NSTAGE) mbar_wait(qfree, qf_ph);
            mbar_wait(empty0 + pp.stage * 8, pp.phase<NG>());
            uint32_t fb = full0 + pp.stage * 8, sb = sbase + pp.stage * STAGE_BYTES;
            if (lane == 0) {
              mbar_expect_tx(fb, 28672);
              tma_load(sb, &p.tm_w2, arow, ks * 32, fb);
              tma_load(sb + 4096, &p.tm_w2, arow + 64, ks * 32, fb);
              tma_load_mc(sb + 8192 + rank * 8192, &p.tm_ut, b * 320 + rank * 128, ks * 32, fb);
              tma_load_mc(sb + 12288 + rank * 8192, &p.tm_ut, b * 320 + rank * 128 + 64, ks * 32, fb);
              if ((ks & 1) == rank) tma_load_mc(sb + 24576, &p.tm_ut, b * 320 + 256, ks * 32, fb);
            }
            pp.next<NG>();
          }
        } else if (type == IT_OP) {
          if (NY > 0) mask_wait(0, (2u << ((NY - 1) >> 2)) - 1, 127u, &g_cnt_u[(lane < 7 ? lane : 0) * 32], ep * 20);
#pragma unroll 1
          for (int ks = 0; ks < NY; ks++) {
            if (pp.stage == NSTAGE) mbar_wait(qfree, qf_ph);
            mbar_wait(empty0 + pp.stage * 8, pp.phase<NG>());
            uint32_t fb = full0 + pp.stage * 8, sb = sbase + pp.stage * STAGE_BYTES;
            if (lane == 0) {
              mbar_expect_tx(fb, STAGE_BYTES);
              tma_load(sb, &p.tm_w2b, arow, ks * 64, fb);
              tma_load(sb + 8192, &p.tm_w2b, arow + 64, ks * 64, fb);
              tma_load_mc(sb + 16384 + rank * 8192, &p.tm_ut_st, b * 128 + rank * 64, ks * 64, fb);
            }
            pp.next<NG>();
          }
          uint32_t o_ok = 0;
          const unsigned* o_ptr = &g_cnt_o[(a * 2 + rank) * 32 + lane];
#pragma unroll 1
          for (int ks = 0; ks < HD / 64; ks++) {
            const int h = p.horder[a * 32 + (ks >> 1)];
            const int k0 = h * DH + (ks & 1) * 64;
            if (pp.stage == NSTAGE) mbar_wait(qfree, qf_ph);
            mbar_wait(empty0 + pp.stage * 8, pp.phase<NG>());
            uint32_t fb = full0 + pp.stage * 8, sb = sbase + pp.stage * STAGE_BYTES;
            if (lane == 0) {
              mbar_expect_tx(fb, STAGE_BYTES);
              tma_load_mc(sb + 16384 + rank * 8192, &p.tm_wo, b * 128 + rank * 64, k0, fb);
            }
            o_ok = mask_wait(o_ok, 1u << h, 0xffffffffu, o_ptr, ep * 2);
            if (lane == 0) tma_load(sb, &p.tm_o_ld, k0, arow, fb);
            pp.next<NG>();
          }
        } else if (type == IT_M1) {
#pragma unroll 1
          for (int ks = 0; ks < SEQ / 64; ks++) {
            ln_ok = mask_wait(ln_ok, 0x10000u << (ks >> 1), 0xffffffffu, ln_ptr, ep * 8);
            if (pp.stage == NSTAGE) mbar_wait(qfree, qf_ph);
            mbar_wait(empty0 + pp.stage * 8, pp.phase<NG>());
            uint32_t fb = full0 + pp.stage * 8, sb = sbase + pp.stage * STAGE_BYTES;
            if (lane == 0) {
              mbar_expect_tx(fb, STAGE_BYTES);
              tma_load(sb, &p.tm_w1, arow, ks * 64, fb);
              tma_load(sb + 8192, &p.tm_w1, arow + 64, ks * 64, fb);
              tma_load_mc(sb + 16384 + rank * 8192, &p.tm_h, b * 128 + rank * 64, ks * 64, fb);
            }
            pp.next<NG>();
          }
        } else {
          qf_ph ^= 1;
          ln_ok = mask_wait(ln_ok, 1u << (a * 2 + rank), 1u << (a * 2 + rank), ln_ptr, ep * 8);
          if (ii == 0 && lane == 0) { TLX(0, 59); }
#pragma unroll 1
          for (int ks = 0; ks < DM / 64; ks++) {
            mbar_wait(empty0 + pp.stage * 8, pp.phase<NA>());
            uint32_t fb = full0 + pp.stage * 8, sb = sbase + pp.stage * STAGE_BYTES;
            if (lane == 0) {
              mbar_expect_tx(fb, STAGE_BYTES);
              tma_load(sb, &p.tm_xn, ks * 64, arow, fb);
              tma_load_mc(sb + 16384 + rank * 8192, &p.tm_wq, c * DH + rank * 64, ks * 64, fb);
            }
            pp.next<NA>();
            if (type == IT_ATTN2 && (ks & 1) == 0) {
              mbar_wait(empty0 + pp.stage * 8, pp.phase<NA>());
              fb = full0 + pp.stage * 8; sb = sbase + pp.stage * STAGE_BYTES;
              if (lane == 0) {
                mbar_expect_tx(fb, STAGE_BYTES);
                tma_load_mc(sb + rank * 16384, &p.tm_wq, b * DH + rank * 64, ks * 64, fb);
                tma_load_mc(sb + rank * 16384 + 8192, &p.tm_wq, b * DH + rank * 64, ks * 64 + 64, fb);
              }
              pp.next<NA>();
            }
          }
          const int nblk = type == IT_ATTN2 ? 32 : 16;
          const uint32_t nx = items[ii + 1];
          const int nh = ((nx >> 13) == IT_ATTN1 || (nx >> 13) == IT_ATTN2) ? (nx >> 5) & 31 : -1;
          const char* pfb = reinterpret_cast<const char*>(a < 4 ? p.kc : p.vc) + ((a & 3) * 2 + rank) * 4096;
          int vrow = 0;
#pragma unroll 1
          for (int blk = 0; blk <= nblk; blk++) {
            const int krow = (blk < 16 ? b : c) * SEQ + (blk & 15) * 128;
            if (blk < nblk) {
              mbar_wait(empty0 + pp.stage * 8, pp.phase<NA>());
              const uint32_t fb = full0 + pp.stage * 8;
              if (lane == 0) {
                mbar_expect_tx(fb, STAGE_BYTES);
                tma_load_mc(sbase + pp.stage * STAGE_BYTES + rank * 16384, &p.tm_k, rank * 64, krow, fb);
              }
              pp.next<NA>();
            }
            if (blk > 0) {
              mbar_wait(empty0 + pp.stage * 8, pp.phase<NA>());
              const uint32_t fb = full0 + pp.stage * 8;
              if (lane == 0) {
                mbar_expect_tx(fb, STAGE_BYTES);
                tma_load_mc(sbase + pp.stage * STAGE_BYTES + rank * 16384, &p.tm_v, rank * 64, vrow, fb);
              }
              pp.next<NA>();
            }
            vrow = krow;
            {
              const int pb = blk + PFD;
              const int ph = pb < 16 ? b : pb < nblk ? c : nh;
              if (ph >= 0 && lane == 0) l2_prefetch(pfb + (size_t)(ph * 16 + (pb & 15)) * 32768);
            }
            if (blk == 4) ln_ok = mask_wait(ln_ok, 0xffffu, 0xffffu, ln_ptr, ep * 8);
          }
        }
      }
    } else {
      if (pw == 1) {
        const uint32_t it = items[0];
        const int type = it >> 13, a = (it >> 10) & 7, b = (it >> 5) & 31, c = it & 31, k = lane;
        if (type == IT_ATTN2) {
          if ((k & 7) != a) {}
          else if (k < 20) tma_prefetch(&p.tm_wq, ((k & 1) ? c : b) * DH + rank * 64, (k >> 1) * 64);
          const char* pfb = reinterpret_cast<const char*>(a < 4 ? p.kc : p.vc) + ((a & 3) * 2 + rank) * 4096;
          if (lane >= 24 && lane < 24 + PFD) l2_prefetch(pfb + (size_t)(b * 16 + lane - 24) * 32768);
        } else if (type == IT_M1 && k < 30 && (k >> 1) % 5 == b) {
          tma_prefetch(&p.tm_w1, (a * 2 + rank) * 128 + (k & 1) * 64, (k >> 1) * 64);
        }
        __syncwarp();
      } else if (pw == 2 && lane < 14) {
        asm volatile("prefetch.tensormap [%0];" ::"l"(&p.tm_xn + lane) : "memory");
      }
      __syncwarp();
      asm volatile("barrier.cluster.wait.aligned;" ::: "memory");
      if (pw == 3) {
       const long long t_entry = clock64();
       if (lane == 0) {
        if (ln_cta) {
          mbar_wait(lnb0, 0);
          TLX(1, 59);
          red_release(&g_cnt_ln[(blockIdx.x >> 3) * 32], 1);
          TLX(0, 57);
          mbar_wait(lnb0 + 8, 0);
          bulk_store(g_h + (size_t)blockIdx.x * 16 * DM, sbase + QB0_OFF, 16 * DM * 2);
          bulk_commit();
          bulk_wait_read0();
        }
        mbar_arrive_local(stf0);
        mbar_arrive_local(stf0 + 16);
        if (ln_cta) {
          bulk_wait0();
          red_release(&g_cnt_ln[(16 + (blockIdx.x >> 3)) * 32], 1);
          TLX(1, 58);
        }
       if (M1_FIRST) prefetch_all(p.w1, SEQ * FF * 2, 300);
       else __nanosleep(10000);
       prefetch_all(p.wq, DM * HD * 2, 1000);
       if (!M1_FIRST) prefetch_all(p.w1, SEQ * FF * 2, 1000);
       if (G_EARLY) prefetch_all(p.w2, SEQ * FF * 2, 1000);
       while (clock64() - t_entry < PF_LATE) __nanosleep(2000);
       if (!G_EARLY) prefetch_all(p.w2, SEQ * FF * 2, 600);
       prefetch_all(p.wo, HD * DM * 2, 600);
       }
      } else if (lane == 0) {
        const int w = pw - 1;
        uint32_t ph = 0;
#pragma unroll 1
        for (int ii = 0; ii < MAXITEMS; ii++) {
          const uint32_t it = items[ii];
          const int type = it >> 13, a = (it >> 10) & 7, b = (it >> 5) & 31, c = it & 31;
          if (type == IT_NONE) break;
          const int mrow = (a * 2 + rank) * 128 + w * 64;
          const uint32_t buf0 = sbase + QB0_OFF + w * 16384;
          if (type == IT_M2) {
            mbar_wait(stq0 + w * 8, ph);
            ph ^= 1;
            const uint32_t keep = keep_s[w];
            for (int ww = 0; ww < 4; ww++) {
              uint4* dst = g_gfrag + ((size_t)((mrow >> 4) + ww) * 40 + b * 20) * 32;
              bulk_store(dst + 16 * 32, buf0 + ww * 2048, 2048);
              bulk_store(dst, sbase + keep * STAGE_BYTES + ww * 8192, 8192);
            }
            bulk_commit();
            bulk_wait_read0();
            mbar_arrive_local(stf0 + w * 16);
            for (int r = 0; r < 2; r++)
              asm volatile("mbarrier.arrive.shared::cluster.b64 _, [%0], 4;" ::"r"(mapa(empty0 + keep * 8, r)) : "memory");
            bulk_wait0();
            red_release(&g_cnt_g[(mrow >> 6) * 2 + b], 1);
            continue;
          }
          if (type == IT_OP) {
            const unsigned ep = *epoch_s;
            if (b <= 2) flag_wait(&g_cnt_g[(mrow >> 6) * 2], ep);
            if (b >= 2) flag_wait(&g_cnt_g[(mrow >> 6) * 2 + 1], ep);
            mbar_expect_tx(ybar + w * 8, 16384);
            for (int ww = 0; ww < 4; ww++)
              asm volatile("cp.async.bulk.shared::cluster.global.mbarrier::complete_tx::bytes [%0], [%1], 4096, [%2];"
                           ::"r"(buf0 + ww * 4096), "l"(g_gfrag + ((size_t)((mrow >> 4) + ww) * 40 + b * 8) * 32), "r"(ybar + w * 8) : "memory");
          }
          const CUtensorMap* tm = type <= IT_ATTN2 ? &p.tm_o_st : type == IT_M1 ? &p.tm_ut_st : &p.tm_out;
          const int nq = type == IT_ATTN2 ? 2 : 1;
#pragma unroll 1
          for (int q = 0; q < nq; q++) {
            const int col = q ? c : b;
            const uint32_t buf = buf0;
            mbar_wait(stq0 + w * 8, ph);
            ph ^= 1;
            if (type != IT_M1 || mrow < FF) {
              tma_store(tm, buf, col * 128, mrow);
              tma_store(tm, buf + 8192, col * 128 + 64, mrow);
            }
            bulk_commit();
            bulk_wait_read0();
            mbar_arrive_local(stf0 + w * 16);
            if (type != IT_OP) {
              bulk_wait0();
              red_release(type == IT_M1 ? &g_cnt_u[a * 32] : &g_cnt_o[(a * 2 + rank) * 32 + col], 1);
            }
          }
        }
      }
    }
  }
  cluster_sync();
}

typedef CUresult (*EncodeFn)(CUtensorMap*, CUtensorMapDataType, cuuint32_t, void*, const cuuint64_t*, const cuuint64_t*,
                             const cuuint32_t*, const cuuint32_t*, CUtensorMapInterleave, CUtensorMapSwizzle,
                             CUtensorMapL2promotion, CUtensorMapFloatOOBfill);

void make_map(EncodeFn enc, CUtensorMap* tm, const void* ptr, uint64_t rows, uint64_t cols, uint32_t box_rows) {
  cuuint64_t dims[2] = {cols, rows};
  cuuint64_t strides[1] = {cols * 2};
  cuuint32_t box[2] = {64, box_rows};
  cuuint32_t es[2] = {1, 1};
  enc(tm, CU_TENSOR_MAP_DATA_TYPE_BFLOAT16, 2, const_cast<void*>(ptr), dims, strides, box, es, CU_TENSOR_MAP_INTERLEAVE_NONE,
      CU_TENSOR_MAP_SWIZZLE_128B, CU_TENSOR_MAP_L2_PROMOTION_L2_256B, CU_TENSOR_MAP_FLOAT_OOB_FILL_NONE);
}

void build_schedule(Params& p) {
  memset(p.items, 0, sizeof(p.items));
  int cls[NCLUSTER];
  {
    int n3 = 0, n2 = 0, n1 = 0;
    for (int c = 0; c < NCLUSTER; c++) {
      if (c % 8 == 3 && n3 < 8) { cls[c] = 3; n3++; }
      else if (c % 32 == 7 && n2 < 2) { cls[c] = 2; n2++; }
      else if (c % 4 == 1 && n1 < 16) { cls[c] = 1; n1++; }
      else cls[c] = 0;
    }
  }
  auto mk = [](int t, int a, int b, int c) { return (uint16_t)((t << 13) | (a << 10) | (b << 5) | c); };
  int cnt[NCLUSTER] = {0}, nm1[NCLUSTER] = {0};
  int m1 = 0;
  for (int r = 0; r < 4; r++)
    for (int c = 0; c < NCLUSTER; c++) {
      int want = cls[c] == 3 ? 4 : cls[c] == 2 ? 2 : 0;
      if (cls[c] == 2 && c > 32) want = 1;
      if (r < want && m1 < 35) { p.items[c * MAXITEMS + (M1_FIRST ? 0 : 1) + nm1[c]++] = mk(IT_M1, m1 / 5, m1 % 5, 0); m1++; }
    }
  struct Slot { int t, c, pos, n; };
  Slot slots[2 * NCLUSTER];
  int ns = 0, nop = 0, nm2 = 0;
  for (int c = 0; c < NCLUSTER; c++) {
    int t = 0;
    if (M1_FIRST) { cnt[c] += nm1[c]; t += nm1[c] * 18; }
    slots[ns++] = Slot{t, c, cnt[c]++, 2};
    t += 79;
    if (!M1_FIRST) { cnt[c] += nm1[c]; t += nm1[c] * 18; }
    if (cls[c] == 1 && G_EARLY) { p.items[c * MAXITEMS + cnt[c]++] = mk(IT_M2, nm2 & 7, nm2 >> 3, 0); nm2++; t += 38 - (NY * 13) / 10; }
    slots[ns++] = Slot{t, c, cnt[c]++, cls[c] == 3 ? 1 : 2};
    if (cls[c] == 1 && !G_EARLY) { p.items[c * MAXITEMS + cnt[c]++] = mk(IT_M2, nm2 & 7, nm2 >> 3, 0); nm2++; }
    if (cls[c] == 0) { p.items[c * MAXITEMS + cnt[c]++] = mk(IT_OP, nop & 7, nop >> 3, 0); nop++; }
  }
  for (int i = 1; i < ns; i++) {
    Slot s = slots[i]; int j = i - 1;
    while (j >= 0 && slots[j].t > s.t) { slots[j + 1] = slots[j]; j--; }
    slots[j + 1] = s;
  }
  int d = 0, sg = 0;
  int tdone[8][32];
  for (int i = 0; i < ns; i++) {
    const Slot& s = slots[i];
    if (s.n == 2) {
      int a = d & 7, hp = d >> 3;
      p.items[s.c * MAXITEMS + s.pos] = mk(IT_ATTN2, a, 2 * hp, 2 * hp + 1);
      tdone[a][2 * hp] = s.t + 43; tdone[a][2 * hp + 1] = s.t + 77;
      d++;
    } else {
      int a = 4 + (sg & 3), h = 30 + (sg >> 2);
      p.items[s.c * MAXITEMS + s.pos] = mk(IT_ATTN1, a, h, h);
      tdone[a][h] = s.t + 40;
      sg++;
    }
  }
  for (int a = 0; a < 8; a++) {
    uint8_t* o = &p.horder[a * 32];
    for (int h = 0; h < 32; h++) {
      int j = h - 1;
      while (j >= 0 && tdone[a][o[j]] > tdone[a][h]) { o[j + 1] = o[j]; j--; }
      o[j + 1] = (uint8_t)h;
    }
  }
}

}

extern "C" void kernel_launch(void* const* d_in, const int* in_sizes, int n_in, void* d_out, int out_size) {
  (void)in_sizes; (void)n_in; (void)out_size;
  static EncodeFn enc = nullptr;
  if (!enc) {
    void* fn = nullptr;
    cudaDriverEntryPointQueryResult qr;
    cudaGetDriverEntryPoint("cuTensorMapEncodeTiled", &fn, cudaEnableDefault, &qr);
    enc = (EncodeFn)fn;
    cudaFuncSetAttribute(mega_kernel, cudaFuncAttributeMaxDynamicSharedMemorySize, SMEM_BYTES);
  }
  void *xn, *h, *o, *ut;
  cudaGetSymbolAddress(&xn, g_xn); cudaGetSymbolAddress(&h, g_h); cudaGetSymbolAddress(&o, g_o);
  cudaGetSymbolAddress(&ut, g_ut);
  Params p;
  make_map(enc, &p.tm_xn, xn, SEQ, DM, 128);
  make_map(enc, &p.tm_wq, d_in[3], DM, HD, 64);
  make_map(enc, &p.tm_k, d_in[1], (uint64_t)NH * SEQ, DH, 128);
  make_map(enc, &p.tm_v, d_in[2], (uint64_t)NH * SEQ, DH, 128);
  make_map(enc, &p.tm_o_st, o, SEQ, HD, 64);
  make_map(enc, &p.tm_o_ld, o, SEQ, HD, 128);
  make_map(enc, &p.tm_wo, d_in[4], HD, DM, 64);
  make_map(enc, &p.tm_w1, d_in[6], SEQ, FF, 64);
  make_map(enc, &p.tm_h, h, SEQ, DM, 64);
  make_map(enc, &p.tm_ut_st, ut, FF, DM, 64);
  make_map(enc, &p.tm_ut, ut, FF, DM, 32);
  make_map(enc, &p.tm_w2, d_in[8], FF, SEQ, 32);
  make_map(enc, &p.tm_out, d_out, SEQ, DM, 64);
  make_map(enc, &p.tm_w2b, d_in[8], FF, SEQ, 64);
  p.x = (const bf16*)d_in[0]; p.b1 = (const bf16*)d_in[7]; p.b2 = (const bf16*)d_in[9];
  p.w1 = (const bf16*)d_in[6]; p.w2 = (const bf16*)d_in[8]; p.wo = (const bf16*)d_in[4];
  p.wq = (const bf16*)d_in[3]; p.kc = (const bf16*)d_in[1]; p.vc = (const bf16*)d_in[2];
  build_schedule(p);
  mega_kernel<<<2 * NCLUSTER, 384, SMEM_BYTES, cudaStreamPerThread>>>(p);
}
```

```cpp
#include <cuda_runtime.h>
#include <cuda_bf16.h>
#include <cuda.h>
#include <stdint.h>
#include <string.h>

typedef __nv_bfloat16 bf16;

namespace {

constexpr int SEQ = 2048, DM = 640, NH = 32, DH = 128, FF = 1728, HD = NH * DH;
constexpr int STAGE_BYTES = 32768;
constexpr int NSTAGE = 5;
constexpr int QB1_OFF = NSTAGE * STAGE_BYTES;
constexpr int QB0_OFF = QB1_OFF + STAGE_BYTES;
constexpr int BAR_OFF = QB0_OFF + STAGE_BYTES;
constexpr int SMEM_BYTES = BAR_OFF + 256 + 1024;
constexpr int NCLUSTER = 66, MAXITEMS = 8;

__device__ __align__(1024) bf16 g_xn[SEQ * DM];
__device__ __align__(1024) bf16 g_h[SEQ * DM];
__device__ __align__(1024) bf16 g_o[SEQ * HD];
__device__ __align__(1024) bf16 g_ut[FF * DM];
__device__ __align__(1024) uint4 g_gfrag[SEQ * DM / 8];
__device__ unsigned g_epoch[2 * NCLUSTER * 8];
__device__ unsigned g_cnt_ln[32 * 32];
__device__ unsigned g_cnt_o[16 * 32];
__device__ unsigned g_cnt_u[7 * 32];
__device__ unsigned g_cnt_g[32 * 2];


struct alignas(64) Params {
  CUtensorMap tm_xn;
  CUtensorMap tm_wq;
  CUtensorMap tm_k;
  CUtensorMap tm_v;
  CUtensorMap tm_o_st;
  CUtensorMap tm_o_ld;
  CUtensorMap tm_wo;
  CUtensorMap tm_w1;
  CUtensorMap tm_h;
  CUtensorMap tm_ut_st;
  CUtensorMap tm_ut;
  CUtensorMap tm_w2;
  CUtensorMap tm_out;
  CUtensorMap tm_w2b;
  CUtensorMap tm_x;
  const bf16* x;
  const bf16* b1;
  const bf16* b2;
  const bf16 *kc, *vc;
  uint16_t items[NCLUSTER * MAXITEMS];
  uint8_t horder[8 * 32];
};

__device__ __forceinline__ uint32_t smem_u32(const void* p) { return (uint32_t)__cvta_generic_to_shared(p); }
__device__ __forceinline__ void mbar_init(uint32_t bar, uint32_t cnt) {
  asm volatile("mbarrier.init.shared::cta.b64 [%0], %1;" ::"r"(bar), "r"(cnt));
}
__device__ __forceinline__ void mbar_expect_tx(uint32_t bar, uint32_t bytes) {
  asm volatile("mbarrier.arrive.expect_tx.shared::cta.b64 _, [%0], %1;" ::"r"(bar), "r"(bytes) : "memory");
}
__device__ __forceinline__ void mbar_wait(uint32_t bar, uint32_t parity) {
  asm volatile(
      "{\n.reg .pred p;\n.reg .u32 n;\n"
      "mbarrier.try_wait.parity.shared::cta.b64 p, [%0], %1;\n"
      "@p bra MW_DONE;\n"
      "mov.u32 n, 0;\n"
      "MW_LOOP:\n"
      "mbarrier.try_wait.parity.shared::cta.b64 p, [%0], %1;\n"
      "@p bra MW_DONE;\n"
      "add.u32 n, n, 1;\n"
      "setp.lt.u32 p, n, 4194304;\n"
      "@p bra MW_LOOP;\n"
      "trap;\n"
      "MW_DONE:\n}\n" ::"r"(bar), "r"(parity) : "memory");
}
__device__ __forceinline__ void red_release(unsigned* p, unsigned v) {
  asm volatile("red.release.gpu.global.add.u32 [%0], %1;" ::"l"(p), "r"(v) : "memory");
}
__device__ __forceinline__ void flag_wait(const unsigned* ptr, unsigned target) {
  asm volatile(
      "{\n.reg .pred p;\n.reg .u32 n, v;\n.reg .s32 d;\n"
      "mov.u32 n, 0;\n"
      "FW_LOOP:\n"
      "ld.acquire.gpu.global.u32 v, [%0];\n"
      "sub.s32 d, v, %1;\n"
      "setp.ge.s32 p, d, 0;\n"
      "@p bra FW_DONE;\n"
      "nanosleep.u32 100;\n"
      "add.u32 n, n, 1;\n"
      "setp.lt.u32 p, n, 4194304;\n"
      "@p bra FW_LOOP;\n"
      "trap;\n"
      "FW_DONE:\n"
      "fence.proxy.async.global;\n}\n" ::"l"(ptr), "r"(target) : "memory");
}
__device__ __forceinline__ uint32_t mask_wait(uint32_t have, uint32_t need, uint32_t watch, const unsigned* lane_ptr, unsigned target) {
  if ((have & need) == need) return have;
  const uint32_t me = (watch >> (threadIdx.x & 31)) & 1;
#pragma unroll 1
  for (uint32_t n = 0;; n++) {
    unsigned v = target - 1;
    asm volatile("{\n.reg .pred p;\nsetp.ne.u32 p, %2, 0;\n@p ld.acquire.gpu.global.u32 %0, [%1];\n}\n" : "+r"(v) : "l"(lane_ptr), "r"(me) : "memory");
    have |= __ballot_sync(0xffffffffu, (int)(v - target) >= 0);
    if ((have & need) == need) break;
    asm volatile("{\n.reg .pred p;\nsetp.gt.u32 p, %0, 4194304;\n@p trap;\nnanosleep.u32 20;\n}\n" ::"r"(n));
  }
  __syncwarp();
  asm volatile("fence.proxy.async.global;" ::: "memory");
  return have;
}
__device__ __forceinline__ void mbar_arrive_local(uint32_t bar) {
  asm volatile("mbarrier.arrive.shared::cta.b64 _, [%0];" ::"r"(bar) : "memory");
}
__device__ __forceinline__ void tma_prefetch(const CUtensorMap* tm, int c0, int c1) {
  asm volatile("cp.async.bulk.prefetch.tensor.2d.L2.global [%0, {%1, %2}];" ::"l"(tm), "r"(c0), "r"(c1) : "memory");
}
__device__ __forceinline__ uint32_t mapa(uint32_t addr, uint32_t cta) {
  uint32_t r;
  asm volatile("mapa.shared::cluster.u32 %0, %1, %2;" : "=r"(r) : "r"(addr), "r"(cta));
  return r;
}
constexpr uint64_t POL_EF = 0x12F0000000000000ull;
#define EL "{\n.reg .pred e;\nelect.sync _|e, 0xffffffff;\n@e "
__device__ __forceinline__ void w_expect(uint32_t bar, uint32_t bytes) {
  asm volatile(EL "mbarrier.arrive.expect_tx.shared::cta.b64 _, [%0], %1;\n}" ::"r"(bar), "r"(bytes) : "memory");
}
template <bool MC, bool EFH>
__device__ __forceinline__ void w_load(uint32_t dst, const CUtensorMap* tm, int c0, int c1, uint32_t bar) {
  if (MC && EFH)
    asm volatile(EL "cp.async.bulk.tensor.2d.shared::cluster.global.mbarrier::complete_tx::bytes.multicast::cluster.L2::cache_hint [%0], [%1, {%3, %4}], [%2], %5, %6;\n}"
                 ::"r"(dst), "l"(tm), "r"(bar), "r"(c0), "r"(c1), "h"((uint16_t)3), "l"(POL_EF) : "memory");
  else if (MC)
    asm volatile(EL "cp.async.bulk.tensor.2d.shared::cluster.global.mbarrier::complete_tx::bytes.multicast::cluster [%0], [%1, {%3, %4}], [%2], %5;\n}"
                 ::"r"(dst), "l"(tm), "r"(bar), "r"(c0), "r"(c1), "h"((uint16_t)3) : "memory");
  else if (EFH)
    asm volatile(EL "cp.async.bulk.tensor.2d.shared::cluster.global.mbarrier::complete_tx::bytes.L2::cache_hint [%0], [%1, {%3, %4}], [%2], %5;\n}"
                 ::"r"(dst), "l"(tm), "r"(bar), "r"(c0), "r"(c1), "l"(POL_EF) : "memory");
  else
    asm volatile(EL "cp.async.bulk.tensor.2d.shared::cluster.global.mbarrier::complete_tx::bytes [%0], [%1, {%3, %4}], [%2];\n}"
                 ::"r"(dst), "l"(tm), "r"(bar), "r"(c0), "r"(c1) : "memory");
}
__device__ __forceinline__ void w_prefetch_ef(const void* ptr) {
  asm volatile(EL "cp.async.bulk.prefetch.L2.global.L2::cache_hint [%0], 4096, %1;\n}" ::"l"(ptr), "l"(POL_EF) : "memory");
}
__device__ __forceinline__ void l2_prefetch_ef(const void* ptr) {
  asm volatile("cp.async.bulk.prefetch.L2.global.L2::cache_hint [%0], 4096, %1;" ::"l"(ptr), "l"(POL_EF) : "memory");
}
__device__ __forceinline__ void tma_store(const CUtensorMap* tm, uint32_t src, int c0, int c1) {
  asm volatile("cp.async.bulk.tensor.2d.global.shared::cta.bulk_group [%0, {%2, %3}], [%1];"
               ::"l"(tm), "r"(src), "r"(c0), "r"(c1) : "memory");
}
__device__ __forceinline__ void bulk_commit() { asm volatile("cp.async.bulk.commit_group;" ::: "memory"); }
__device__ __forceinline__ void bulk_wait_read0() { asm volatile("cp.async.bulk.wait_group.read 0;" ::: "memory"); }
__device__ __forceinline__ void bulk_wait0() { asm volatile("cp.async.bulk.wait_group 0;" ::: "memory"); }
__device__ __forceinline__ void fence_async_smem() { asm volatile("fence.proxy.async.shared::cta;" ::: "memory"); }
__device__ __forceinline__ void named_sync(int id, int n) { asm volatile("bar.sync %0, %1;" ::"r"(id), "r"(n) : "memory"); }
__device__ __forceinline__ void named_arrive(int id, int n) { asm volatile("bar.arrive %0, %1;" ::"r"(id), "r"(n) : "memory"); }
__device__ __forceinline__ void stmatrix_x4(uint32_t addr, uint32_t r0, uint32_t r1, uint32_t r2, uint32_t r3) {
  asm volatile("stmatrix.sync.aligned.m8n8.x4.shared.b16 [%0], {%1, %2, %3, %4};"
               ::"r"(addr), "r"(r0), "r"(r1), "r"(r2), "r"(r3) : "memory");
}
__device__ __forceinline__ uint32_t pack_bf16(float lo, float hi) {
  uint32_t r;
  asm("cvt.rn.bf16x2.f32 %0, %1, %2;" : "=r"(r) : "f"(hi), "f"(lo));
  return r;
}
__device__ __forceinline__ float ex2(float x) {
  float r;
  asm("ex2.approx.ftz.f32 %0, %1;" : "=f"(r) : "f"(x));
  return r;
}
__device__ __forceinline__ float tanh_f(float x) {
  float r;
  asm("tanh.approx.f32 %0, %1;" : "=f"(r) : "f"(x));
  return r;
}
__device__ __forceinline__ void bulk_store(void* dst, uint32_t src, uint32_t bytes) {
  asm volatile("cp.async.bulk.global.shared::cta.bulk_group [%0], [%1], %2;" ::"l"(dst), "r"(src), "r"(bytes) : "memory");
}
__device__ __forceinline__ float rbf(float x) { return __bfloat162float(__float2bfloat16(x)); }

#define WG_FENCE() asm volatile("wgmma.fence.sync.aligned;" ::: "memory")
#define WG_COMMIT() asm volatile("wgmma.commit_group.sync.aligned;" ::: "memory")
#define WG_WAIT(n) asm volatile("wgmma.wait_group.sync.aligned %0;" ::"n"(n) : "memory")

#define R8(a, o) "+f"(a[o + 0]), "+f"(a[o + 1]), "+f"(a[o + 2]), "+f"(a[o + 3]), "+f"(a[o + 4]), "+f"(a[o + 5]), "+f"(a[o + 6]), "+f"(a[o + 7])
#define R64(a) R8(a, 0), R8(a, 8), R8(a, 16), R8(a, 24), R8(a, 32), R8(a, 40), R8(a, 48), R8(a, 56)
#define L64 "{%0,%1,%2,%3,%4,%5,%6,%7,%8,%9,%10,%11,%12,%13,%14,%15,%16,%17,%18,%19,%20,%21,%22,%23,%24,%25,%26,%27,%28,%29,%30,%31," \
            "%32,%33,%34,%35,%36,%37,%38,%39,%40,%41,%42,%43,%44,%45,%46,%47,%48,%49,%50,%51,%52,%53,%54,%55,%56,%57,%58,%59,%60,%61,%62,%63}"

__device__ __forceinline__ uint64_t make_desc(uint32_t addr, uint32_t lbo) {
  uint64_t d;
  asm("mov.b64 %0, {%1, %2};" : "=l"(d) : "r"((addr >> 4) + ((lbo >> 4) << 16)), "r"(64u | (1u << 30)));
  return d;
}
#define W8(a, o) "=f"(a[o + 0]), "=f"(a[o + 1]), "=f"(a[o + 2]), "=f"(a[o + 3]), "=f"(a[o + 4]), "=f"(a[o + 5]), "=f"(a[o + 6]), "=f"(a[o + 7])
#define W64(a) W8(a, 0), W8(a, 8), W8(a, 16), W8(a, 24), W8(a, 32), W8(a, 40), W8(a, 48), W8(a, 56)
#define R96(a) R64(a), R8(a, 64), R8(a, 72), R8(a, 80), R8(a, 88)
#define L96 "{%0,%1,%2,%3,%4,%5,%6,%7,%8,%9,%10,%11,%12,%13,%14,%15,%16,%17,%18,%19,%20,%21,%22,%23,%24,%25,%26,%27,%28,%29,%30,%31," \
            "%32,%33,%34,%35,%36,%37,%38,%39,%40,%41,%42,%43,%44,%45,%46,%47,%48,%49,%50,%51,%52,%53,%54,%55,%56,%57,%58,%59,%60,%61,%62,%63," \
            "%64,%65,%66,%67,%68,%69,%70,%71,%72,%73,%74,%75,%76,%77,%78,%79,%80,%81,%82,%83,%84,%85,%86,%87,%88,%89,%90,%91,%92,%93,%94,%95}"
template <int TA, int TB, int OA, int OB>
__device__ __forceinline__ void wgmma_ss(float (&d)[64], uint64_t a, uint64_t b) {
  asm volatile("{\n.reg .b64 da, db;\nadd.s64 da, %64, %66;\nadd.s64 db, %65, %67;\n"
               "wgmma.mma_async.sync.aligned.m64n128k16.f32.bf16.bf16 " L64 ", da, db, 1, 1, 1, %68, %69;\n}\n"
               : R64(d) : "l"(a), "l"(b), "n"(OA), "n"(OB), "n"(TA), "n"(TB));
}
template <int TA, int TB>
__device__ __forceinline__ void wgmma_ss_first(float (&d)[64], uint64_t a, uint64_t b) {
  asm volatile("wgmma.mma_async.sync.aligned.m64n128k16.f32.bf16.bf16 " L64 ", %64, %65, 0, 1, 1, %66, %67;\n"
               : W64(d) : "l"(a), "l"(b), "n"(TA), "n"(TB));
}
template <int TA, int TB, int OA = 0>
__device__ __forceinline__ void wgmma_ss_p(float (&d)[64], uint64_t a, uint64_t b, int acc) {
  asm volatile("{\n.reg .pred p;\n.reg .b64 da;\nsetp.ne.b32 p, %66, 0;\nadd.s64 da, %64, %69;\n"
               "wgmma.mma_async.sync.aligned.m64n128k16.f32.bf16.bf16 " L64 ", da, %65, p, 1, 1, %67, %68;\n}\n"
               : R64(d) : "l"(a), "l"(b), "r"(acc), "n"(TA), "n"(TB), "n"(OA));
}
template <int TB, int OB>
__device__ __forceinline__ void wgmma_rs(float (&d)[64], const uint32_t* a, uint64_t b) {
  asm volatile("{\n.reg .b64 db;\nadd.s64 db, %68, %69;\n"
               "wgmma.mma_async.sync.aligned.m64n128k16.f32.bf16.bf16 " L64 ", {%64,%65,%66,%67}, db, 1, 1, 1, %70;\n}\n"
               : R64(d) : "r"(a[0]), "r"(a[1]), "r"(a[2]), "r"(a[3]), "l"(b), "n"(OB), "n"(TB));
}
template <int TB>
__device__ __forceinline__ void wgmma_rs_p(float (&d)[64], const uint32_t* a, uint64_t b, int acc) {
  asm volatile("{\n.reg .pred p;\nsetp.ne.b32 p, %69, 0;\n"
               "wgmma.mma_async.sync.aligned.m64n128k16.f32.bf16.bf16 " L64 ", {%64,%65,%66,%67}, %68, p, 1, 1, %70;\n}\n"
               : R64(d) : "r"(a[0]), "r"(a[1]), "r"(a[2]), "r"(a[3]), "l"(b), "r"(acc), "n"(TB));
}
template <int TA, int TB, int OA, int OB>
__device__ __forceinline__ void wgmma_ss192(float (&d)[96], uint64_t a, uint64_t b, int acc) {
  asm volatile("{\n.reg .pred p;\n.reg .b64 da, db;\nsetp.ne.b32 p, %102, 0;\nadd.s64 da, %96, %98;\nadd.s64 db, %97, %99;\n"
               "wgmma.mma_async.sync.aligned.m64n192k16.f32.bf16.bf16 " L96 ", da, db, p, 1, 1, %100, %101;\n}\n"
               : R96(d) : "l"(a), "l"(b), "n"(OA), "n"(OB), "n"(TA), "n"(TB), "r"(acc));
}
#define W96(a) W64(a), W8(a, 64), W8(a, 72), W8(a, 80), W8(a, 88)
template <int TA, int TB, int OB>
__device__ __forceinline__ void wgmma_ss192_first(float (&d)[96], uint64_t a, uint64_t b) {
  asm volatile("{\n.reg .b64 db;\nadd.s64 db, %97, %98;\n"
               "wgmma.mma_async.sync.aligned.m64n192k16.f32.bf16.bf16 " L96 ", %96, db, 0, 1, 1, %99, %100;\n}\n"
               : W96(d) : "l"(a), "l"(b), "n"(OB), "n"(TA), "n"(TB));
}
template <int N>
__device__ __forceinline__ void undef_regs(float (&d)[N]) {
#pragma unroll
  for (int i = 0; i < N; i++) d[i] = 0.f;
}
template <int N>
__device__ __forceinline__ void fence_regs(float (&d)[N]) {
#pragma unroll
  for (int i = 0; i < N; i++) asm volatile("" : "+f"(d[i])::"memory");
}
template <int N>
__device__ __forceinline__ void fence_regs(uint32_t (&d)[N]) {
#pragma unroll
  for (int i = 0; i < N; i++) asm volatile("" : "+r"(d[i])::"memory");
}

__device__ __forceinline__ float half_sum(float v) {
#pragma unroll
  for (int o = 8; o; o >>= 1) v += __shfl_xor_sync(0xffffffffu, v, o);
  return v;
}
__device__ __forceinline__ void ln_rows(uint4 (&u)[5], uint4* gdst, uint32_t sdst, uint32_t bar0, int pass0, bool first_warp) {
#pragma unroll 1
  for (int pass = pass0;; pass++) {
    float v[40];
    float s[4] = {0.f, 0.f, 0.f, 0.f};
#pragma unroll
    for (int i = 0; i < 5; i++) {
      const uint32_t w[4] = {u[i].x, u[i].y, u[i].z, u[i].w};
#pragma unroll
      for (int q = 0; q < 4; q++) {
        v[8 * i + 2 * q] = __uint_as_float(w[q] << 16);
        v[8 * i + 2 * q + 1] = __uint_as_float(w[q] & 0xffff0000u);
        s[q] += v[8 * i + 2 * q] + v[8 * i + 2 * q + 1];
      }
    }
    const float mean = half_sum((s[0] + s[1]) + (s[2] + s[3])) * (1.f / DM);
    const float m = rbf(mean);
    float qq[4] = {0.f, 0.f, 0.f, 0.f};
#pragma unroll
    for (int i = 0; i < 40; i++) { v[i] -= m; qq[i & 3] = fmaf(v[i], v[i], qq[i & 3]); }
#pragma unroll
    for (int i = 0; i < 20; i++) {
      const uint32_t c = pack_bf16(v[2 * i], v[2 * i + 1]);
      v[2 * i] = __uint_as_float(c << 16); v[2 * i + 1] = __uint_as_float(c & 0xffff0000u);
    }
    const float var = fmaxf(fmaf(mean - m, m - mean, half_sum((qq[0] + qq[1]) + (qq[2] + qq[3])) * (1.f / DM)), 0.f);
    float den, inv;
    asm("sqrt.approx.ftz.f32 %0, %1;" : "=f"(den) : "f"(rbf(rbf(var) + 1e-5f)));
    asm("rcp.approx.ftz.f32 %0, %1;" : "=f"(inv) : "f"(rbf(den)));
    {
      if (pass == 0) {
        const float sc = inv * (0.08838834764831845f * 1.4426950408889634f);
#pragma unroll
        for (int i = 0; i < 5; i++)
          gdst[i * 16] = make_uint4(pack_bf16(v[8 * i] * sc, v[8 * i + 1] * sc), pack_bf16(v[8 * i + 2] * sc, v[8 * i + 3] * sc),
                                    pack_bf16(v[8 * i + 4] * sc, v[8 * i + 5] * sc), pack_bf16(v[8 * i + 6] * sc, v[8 * i + 7] * sc));
        __syncwarp();
        if ((threadIdx.x & 31) == 0) mbar_arrive_local(bar0);
        if (first_warp) {
          mbar_wait(bar0, 0);
          if (threadIdx.x == 0) { red_release(&g_cnt_ln[(blockIdx.x >> 3) * 32], 1); }
        }
        __syncwarp();
      }
    }
#pragma unroll
    for (int i = 0; i < 5; i++) {
      uint32_t w[4];
#pragma unroll
      for (int q = 0; q < 4; q++) w[q] = pack_bf16(v[8 * i + 2 * q] * inv, v[8 * i + 2 * q + 1] * inv);
      u[i] = make_uint4(w[0], w[1], w[2], w[3]);
      if (pass == 1) asm volatile("st.shared.v4.b32 [%0], {%1,%2,%3,%4};" ::"r"(sdst + i * 256), "r"(w[0]), "r"(w[1]), "r"(w[2]), "r"(w[3]) : "memory");
    }
    if (pass == 1) {
      fence_async_smem();
      __syncwarp();
      if ((threadIdx.x & 31) == 0) mbar_arrive_local(bar0 + 8);
    }
    __syncwarp();
    if (pass >= 1) break;
  }
}

constexpr int NA = NSTAGE, NG = NSTAGE + 1;
struct Pipe {
  uint32_t so, lap;
  template <int N> __device__ __forceinline__ void next() {
    so += 8;
    if (so == 8 * N) { so = 0; lap ^= 1; }
  }
  __device__ __forceinline__ void enter_attn() { if (so == 8 * NA) { so = 0; lap ^= 1; } }
};
constexpr uint32_t SO_DUMMY = 56;
__device__ __forceinline__ uint64_t sdesc(uint32_t addr, uint32_t lbo, uint32_t so) {
  uint64_t d;
  asm("mov.b64 %0, {%1, %2};" : "=l"(d) : "r"(((addr >> 4) + ((lbo >> 4) << 16)) + so * 256), "r"(64u | (1u << 30)));
  return d;
}

enum { IT_NONE = 0, IT_ATTN1 = 1, IT_ATTN2 = 2, IT_M1 = 3, IT_M2 = 4, IT_OP = 5 };

__device__ __forceinline__ void release_stage(uint32_t empty_mapped, uint32_t so, int lane) {
  asm volatile("{\n.reg .pred p;\nsetp.lt.s32 p, %1, 2;\n@p mbarrier.arrive.shared::cluster.b64 _, [%0];\n}\n"
               ::"r"(empty_mapped + so), "r"(lane) : "memory");
}
__device__ __forceinline__ void release_stage2(uint32_t empty_mapped, uint32_t so, int lane) {
  asm volatile("{\n.reg .pred p;\nsetp.lt.s32 p, %1, 2;\n@p mbarrier.arrive.shared::cluster.b64 _, [%0], 2;\n}\n"
               ::"r"(empty_mapped + so), "r"(lane) : "memory");
}

template <int TA, bool ZEROED>
__device__ __forceinline__ void mma_k64(float (&acc)[64], uint64_t a, uint64_t b, int accum) {
  constexpr int SA = TA ? 128 : 2;
  if (ZEROED) wgmma_ss<TA, 1, 0, 0>(acc, a, b); else wgmma_ss_p<TA, 1>(acc, a, b, accum);
  wgmma_ss<TA, 1, SA, 128>(acc, a, b);
  wgmma_ss<TA, 1, 2 * SA, 256>(acc, a, b);
  wgmma_ss<TA, 1, 3 * SA, 384>(acc, a, b);
}
template <int TA>
__device__ __forceinline__ void mma_k64_first(float (&acc)[64], uint64_t a, uint64_t b) {
  constexpr int SA = TA ? 128 : 2;
  wgmma_ss_first<TA, 1>(acc, a, b);
  wgmma_ss<TA, 1, SA, 128>(acc, a, b);
  wgmma_ss<TA, 1, 2 * SA, 256>(acc, a, b);
  wgmma_ss<TA, 1, 3 * SA, 384>(acc, a, b);
}
template <int TA, bool ZEROED>
__device__ __forceinline__ void gemm_kstep(float (&acc)[64], uint32_t dbase, uint32_t so, int wg, int accum) {
  mma_k64<TA, ZEROED>(acc, sdesc(dbase + wg * 8192, TA ? 8192 : 16, so), sdesc(dbase + 16384, 8192, so), accum);
}

template <int TA, int NR, bool DRAIN, int KZ = -1>
__device__ __forceinline__ void gemm_loop(float (&acc)[64], int ks0, int ksteps, uint32_t& prev, Pipe& pp, uint32_t sbase,
                                          uint32_t full0, uint32_t empty_mapped, int wg, int lane) {
#pragma unroll 1
  for (int ks = ks0; ks < ksteps; ks++) {
    mbar_wait(full0 + pp.so, pp.lap);
    WG_FENCE();
    gemm_kstep<TA, (KZ < 0)>(acc, sbase, pp.so, wg, ks - KZ);
    WG_COMMIT();
    WG_WAIT(1);
    release_stage(empty_mapped, prev, lane);
    prev = pp.so;
    pp.template next<NR>();
  }
  if (DRAIN) {
    WG_WAIT(0);
    fence_regs(acc);
    release_stage(empty_mapped, prev, lane);
  }
}

__device__ __forceinline__ void stage_tile(const uint32_t (&r)[32], uint32_t buf, int warp_in_wg, int lane) {
  int mi = lane >> 3;
  int row = warp_in_wg * 16 + (mi & 1) * 8 + (lane & 7);
  uint32_t rowaddr = buf + row * 128;
#pragma unroll
  for (int kk = 0; kk < 8; kk++) {
    int chunk = ((2 * kk) & 7) + (mi >> 1);
    uint32_t addr = rowaddr + (kk >> 2) * 8192 + ((chunk ^ (lane & 7)) << 4);
    stmatrix_x4(addr, r[4 * kk], r[4 * kk + 1], r[4 * kk + 2], r[4 * kk + 3]);
  }
}


__device__ __forceinline__ float quad_max(float v) {
  v = fmaxf(v, __shfl_xor_sync(0xffffffffu, v, 1));
  return fmaxf(v, __shfl_xor_sync(0xffffffffu, v, 2));
}
__device__ __forceinline__ float quad_sum(float v) {
  v += __shfl_xor_sync(0xffffffffu, v, 1);
  return v + __shfl_xor_sync(0xffffffffu, v, 2);
}

__device__ __forceinline__ void exp_block(const float (&S)[64], uint32_t (&P)[32], float& bs0, float& bs1) {
  float a0 = 0.f, a1 = 0.f, c0 = 0.f, c1 = 0.f;
#pragma unroll
  for (int i = 0; i < 16; i++) {
    float p0 = ex2(S[4 * i + 0]), p1 = ex2(S[4 * i + 1]), p2 = ex2(S[4 * i + 2]), p3 = ex2(S[4 * i + 3]);
    if (i == 0) { a0 = p0; c0 = p1; a1 = p2; c1 = p3; }
    else { a0 += p0; c0 += p1; a1 += p2; c1 += p3; }
    P[2 * i] = pack_bf16(p0, p1);
    P[2 * i + 1] = pack_bf16(p2, p3);
  }
  bs0 = a0 + c0; bs1 = a1 + c1;
}
__device__ __forceinline__ void row_max(const float (&S)[64], float& x0, float& x1) {
  float a0 = fmaxf(S[0], S[1]), a1 = fmaxf(S[2], S[3]);
#pragma unroll
  for (int i = 1; i < 16; i++) {
    a0 = fmaxf(a0, fmaxf(S[4 * i], S[4 * i + 1]));
    a1 = fmaxf(a1, fmaxf(S[4 * i + 2], S[4 * i + 3]));
  }
  x0 = quad_max(a0); x1 = quad_max(a1);
}

struct SmState { float m0, m1, l0, l1; bool sub; };
constexpr float BS_HI = 1099511627776.f;
constexpr float BS_LO = 5.9604644775390625e-8f;

__device__ __forceinline__ void issue_qk(float (&S)[64], uint64_t q, uint64_t k) {
  wgmma_ss_first<0, 0>(S, q, k);
  wgmma_ss<0, 0, 2, 2>(S, q, k); wgmma_ss<0, 0, 4, 4>(S, q, k); wgmma_ss<0, 0, 6, 6>(S, q, k);
  wgmma_ss<0, 0, 512, 1024>(S, q, k); wgmma_ss<0, 0, 514, 1026>(S, q, k); wgmma_ss<0, 0, 516, 1028>(S, q, k); wgmma_ss<0, 0, 518, 1030>(S, q, k);
}
__device__ __forceinline__ void issue_pv(float (&O)[64], const uint32_t (&P)[32], uint64_t v, int acc, int other) {
  wgmma_rs_p<1>(O, &P[0], v, acc);
  wgmma_rs<1, 128>(O, &P[4], v); wgmma_rs<1, 256>(O, &P[8], v); wgmma_rs<1, 384>(O, &P[12], v);
  wgmma_rs<1, 512>(O, &P[16], v); wgmma_rs<1, 640>(O, &P[20], v);
  named_arrive(other, 256);
  wgmma_rs<1, 768>(O, &P[24], v); wgmma_rs<1, 896>(O, &P[28], v);
}

__device__ __forceinline__ bool softmax_block(float (&S)[64], uint32_t (&P)[32], SmState& st, bool first, float& f0, float& f1) {
  float d0 = st.m0, d1 = st.m1, bs0, bs1;
  const float lo = first ? BS_LO : 0.f;
  bool resc = false;
#pragma unroll 1
  for (int pass = 0;; pass++) {
    if (st.sub) {
#pragma unroll
      for (int i = 0; i < 16; i++) { S[4 * i] -= d0; S[4 * i + 1] -= d0; S[4 * i + 2] -= d1; S[4 * i + 3] -= d1; }
    }
    exp_block(S, P, bs0, bs1);
    if (!__any_sync(0xffffffffu, !(fmaxf(bs0, bs1) <= BS_HI && fminf(bs0, bs1) >= lo)) || pass) break;
    row_max(S, d0, d1);
    if (!first) { d0 = fmaxf(d0, 0.f); d1 = fmaxf(d1, 0.f); }
    if (d0 == -INFINITY) d0 = 0.f;
    if (d1 == -INFINITY) d1 = 0.f;
    st.m0 += d0; st.m1 += d1; st.sub = true;
    if (!first) {
      f0 = ex2(-d0); f1 = ex2(-d1);
      st.l0 *= f0; st.l1 *= f1;
      resc = true;
    }
  }
  st.l0 += bs0; st.l1 += bs1;
  return resc;
}
__device__ __forceinline__ void pack_scaled(const float (&A)[64], uint32_t (&R)[32], float s0, float s1) {
#pragma unroll
  for (int i = 0; i < 16; i++) {
    R[2 * i] = pack_bf16(A[4 * i] * s0, A[4 * i + 1] * s0);
    R[2 * i + 1] = pack_bf16(A[4 * i + 2] * s1, A[4 * i + 3] * s1);
  }
}

template <bool ODD>
__device__ __forceinline__ void attn_step(float (&S)[64], float (&O)[64], uint32_t (&Pc)[32], uint32_t (&Pn)[32],
                                          uint32_t qaddr, SmState& st, int acc, Pipe& pp, uint32_t sbase,
                                          uint32_t full0, uint32_t empty_mapped, int wg, int lane,
                                          bool special, uint32_t obuf, uint32_t obar, bool lastqk = false) {
  uint32_t ks = pp.so;
  mbar_wait(full0 + pp.so, pp.lap);
  pp.next<NA>();
  uint32_t vs = pp.so;
  mbar_wait(full0 + pp.so, pp.lap);
  pp.next<NA>();
  named_sync(1 + wg, 256);
  WG_FENCE();
  issue_qk(S, make_desc(qaddr, 16), sdesc(sbase, 16, ks));
  WG_COMMIT();
  float f0 = 1.f, f1 = 1.f;
  if (special) {
    if (!ODD) {
      stage_tile(Pn, obuf, (threadIdx.x >> 5) & 3, lane);
      fence_async_smem();
      if (obar) named_arrive(obar, 160);
    } else {
      f0 = __fdividef(1.f, quad_sum(st.l0)); f1 = __fdividef(1.f, quad_sum(st.l1));
      st.m0 = st.m1 = st.l0 = st.l1 = 0.f; st.sub = false;
    }
  }
  WG_FENCE();
  issue_pv(O, Pc, sdesc(sbase, 16384, vs), acc, 2 - wg);
  WG_COMMIT();
  WG_WAIT(1);
  fence_regs(S);
  release_stage(empty_mapped, ks, lane);
  if (!ODD && lastqk) release_stage(empty_mapped, 8 * NA, lane);
  const bool resc = softmax_block(S, Pn, st, ODD && special, f0, f1);
  WG_WAIT(0);
  fence_regs(O);
  fence_regs(Pc);
  release_stage(empty_mapped, vs, lane);
  if (resc) {
#pragma unroll
    for (int i = 0; i < 16; i++) { O[4 * i] *= f0; O[4 * i + 1] *= f0; O[4 * i + 2] *= f1; O[4 * i + 3] *= f1; }
  }
  if (ODD && special) pack_scaled(O, Pc, f0, f1);
}

__device__ __forceinline__ float silu_f(float v) {
  float h = 0.5f * v;
  return fmaf(h, tanh_f(h), h);
}
__device__ __forceinline__ float gelu_f(float v) {
  float z = v * fmaf(v * v, 0.044715f * 0.7978845608028654f, 0.7978845608028654f);
  float h = 0.5f * v;
  return fmaf(h, tanh_f(z), h);
}

template <int N>
__device__ __forceinline__ void gelu_inplace(uint32_t addr) {
  uint32_t v[4 * N];
#pragma unroll
  for (int c = 0; c < N; c++)
    asm volatile("ld.shared.v4.b32 {%0,%1,%2,%3}, [%4];" : "=r"(v[4 * c]), "=r"(v[4 * c + 1]), "=r"(v[4 * c + 2]), "=r"(v[4 * c + 3]) : "r"(addr + c * 512) : "memory");
#pragma unroll
  for (int i = 0; i < 4 * N; i++) v[i] = pack_bf16(gelu_f(__uint_as_float(v[i] << 16)), gelu_f(__uint_as_float(v[i] & 0xffff0000u)));
#pragma unroll
  for (int c = 0; c < N; c++)
    asm volatile("st.shared.v4.b32 [%0], {%1,%2,%3,%4};" ::"r"(addr + c * 512), "r"(v[4 * c]), "r"(v[4 * c + 1]), "r"(v[4 * c + 2]), "r"(v[4 * c + 3]) : "memory");
}
__device__ __forceinline__ void qp_group(float (&acc)[64], uint64_t x, uint64_t w) {
  mma_k64<0, true>(acc, x, w, 1);
}

constexpr int NY = 4;
constexpr int GOK = 256;
constexpr int WPRE = 3;
constexpr int ST0_2 = 4;
constexpr int ST0_1 = 2;
constexpr int PFD = 3;

__global__ void __cluster_dims__(2, 1, 1) __launch_bounds__(384, 1) mega_kernel(const __grid_constant__ Params p) {
  extern __shared__ uint8_t smem_raw[];
  const uint32_t sbase = (smem_u32(smem_raw) + 1023) & ~1023u;
  const uint32_t full0 = sbase + BAR_OFF;
  const uint32_t empty0 = full0 + 64;
  const uint32_t gobar = full0 + 128;
  const uint32_t stf0 = full0 + 144;
  const uint32_t lnb0 = full0 + 176;
  const uint32_t ybar = full0 + 200;
  volatile unsigned* epoch_s = reinterpret_cast<volatile unsigned*>(smem_raw + (sbase - smem_u32(smem_raw)) + BAR_OFF + 224);
  const int tid = threadIdx.x;
  const int warp = __shfl_sync(0xffffffffu, tid >> 5, 0);
  const int wg = warp >> 2;
  const int lane = tid & 31;
  uint32_t rank;
  asm volatile("mov.u32 %0, %%cluster_ctarank;" : "=r"(rank));
  const int cluster_id = blockIdx.x >> 1;
  const uint16_t* items = p.items + cluster_id * MAXITEMS;

  uint4 xr[5];
#pragma unroll
  for (int i = 0; i < 5; i++) xr[i] = make_uint4(0, 0, 0, 0);
  const bool ln_cta = blockIdx.x < 128;
  if (wg < 2 && ln_cta) {
    const uint4* src = reinterpret_cast<const uint4*>(p.x + (size_t)(blockIdx.x * 16 + (tid >> 4)) * DM);
#pragma unroll
    for (int i = 0; i < 5; i++)
      asm volatile("ld.global.nc.v4.u32 {%0,%1,%2,%3}, [%4];" : "=r"(xr[i].x), "=r"(xr[i].y), "=r"(xr[i].z), "=r"(xr[i].w) : "l"(src + (lane & 15) + i * 16));
  }
  asm volatile("" ::: "memory");
  const uint32_t it0 = __shfl_sync(0xffffffffu, (uint32_t)items[0], 0);
  const uint32_t st0 = (it0 >> 13) == IT_ATTN2 ? ST0_2 : ST0_1;
  if (tid == 256) {
    for (int i = 0; i < NSTAGE + 1; i++) { mbar_init(full0 + i * 8, 1); mbar_init(empty0 + i * 8, 16); }
    for (int i = 0; i < 2; i++) { mbar_init(lnb0 + i * 8, 8); }
    for (int i = 0; i < 4; i++) mbar_init(stf0 + i * 8, 1);
    mbar_init(empty0 + SO_DUMMY, 1u << 19);
    for (uint32_t i = 0; i < st0; i++) {
      mbar_arrive_local(full0 + i * 8);
      asm volatile("mbarrier.arrive.shared::cta.b64 _, [%0], 16;" ::"r"(empty0 + i * 8) : "memory");
    }
    mbar_init(gobar, 1); mbar_init(ybar, 1); mbar_init(ybar + 8, 1);
    asm volatile("fence.mbarrier_init.release.cluster;" ::: "memory");
  }
  __syncthreads();
  asm volatile("barrier.cluster.arrive.relaxed.aligned;" ::: "memory");

  if (warp == 8) {
    const int b = (it0 >> 5) & 31, c = it0 & 31;
    const bool two = (it0 >> 13) == IT_ATTN2;
    asm volatile("barrier.cluster.wait.aligned;" ::: "memory");
#pragma unroll 1
    for (int st = 0; st < WPRE; st++) {
      const uint32_t sl = (st0 + st) % NG, fb = full0 + sl * 8, sb = sbase + sl * STAGE_BYTES;
      w_expect(fb, STAGE_BYTES);
      if (two && st % 3 == 1) {
        w_load<1, 1>(sb + rank * 16384, &p.tm_wq, b * DH + rank * 64, (st / 3) * 128, fb);
        w_load<1, 1>(sb + rank * 16384 + 8192, &p.tm_wq, b * DH + rank * 64, (st / 3) * 128 + 64, fb);
      } else {
        w_load<1, 1>(sb + 16384 + rank * 8192, &p.tm_wq, c * DH + rank * 64, (two ? st - (st + 1) / 3 : st) * 64, fb);
      }
    }
  }
  if (ln_cta && (wg < 2 || warp == 10))
      ln_rows(xr, reinterpret_cast<uint4*>(g_xn + (size_t)(blockIdx.x * 16 + (tid >> 4)) * DM) + (lane & 15),
              sbase + QB0_OFF + (tid >> 4) * (DM * 2) + (lane & 15) * 16, lnb0, wg < 2 ? 0 : 2, warp == 0);

  if (wg < 2) {
    asm volatile("setmaxnreg.inc.sync.aligned.u32 240;");
    asm volatile("barrier.cluster.wait.aligned;" ::: "memory");
    Pipe pp; pp.so = st0 * 8; pp.lap = 0;
    const uint32_t empty_mapped = mapa(empty0, lane & 1);
    const uint32_t dbase = sbase & 0x3FFFF;
    const int warp_in_wg = (tid >> 5) & 3;
    const uint32_t qbuf = sbase + QB0_OFF + wg * 16384;
    const int r0 = warp_in_wg * 16 + (lane >> 2);
    const uint32_t stf = stf0 + wg * 16;
    uint32_t stf_ph0 = 0;
    if (wg == 1) named_arrive(1, 256);
    bool after_attn = false;
    int gpend = 0;
    uint32_t it = it0;

#pragma unroll 1
    for (int ii = 0;; ii++) {
      const int type = it >> 13, a = (it >> 10) & 7;
      if (type == IT_NONE) break;
      const int mrow = (a * 2 + rank) * 128 + wg * 64;
      if (type == IT_M2) {
        float S[64], T[96];
        uint32_t prev = pp.so;
        {
          mbar_wait(full0 + pp.so, pp.lap);
          const uint64_t da = sdesc(dbase + wg * 4096, 4096, pp.so), db = sdesc(dbase + 8192, 4096, pp.so);
          WG_FENCE();
          wgmma_ss_first<1, 1>(S, da, db);
          wgmma_ss192_first<1, 1, 512>(T, da, db);
          wgmma_ss<1, 1, 128, 128>(S, da, db);
          wgmma_ss192<1, 1, 128, 640>(T, da, db, 1);
          WG_COMMIT();
          pp.next<NA>();
        }
        uint32_t br0 = __ldg(reinterpret_cast<const unsigned short*>(p.b2) + mrow + r0);
        uint32_t br1 = __ldg(reinterpret_cast<const unsigned short*>(p.b2) + mrow + r0 + 8);
#pragma unroll 1
        for (int ks = 2 * NY + 1; ks < FF / 32; ks++) {
          mbar_wait(full0 + pp.so, pp.lap);
          const uint64_t da = sdesc(dbase + wg * 4096, 4096, pp.so), db = sdesc(dbase + 8192, 4096, pp.so);
          WG_FENCE();
          wgmma_ss<1, 1, 0, 0>(S, da, db);
          wgmma_ss192<1, 1, 0, 512>(T, da, db, 1);
          wgmma_ss<1, 1, 128, 128>(S, da, db);
          wgmma_ss192<1, 1, 128, 640>(T, da, db, 1);
          WG_COMMIT();
          WG_WAIT(1);
          release_stage(empty_mapped, prev, lane);
          prev = pp.so;
          pp.next<NG>();
        }
        WG_WAIT(0);
        fence_regs(S);
        fence_regs(T);
        asm volatile("" : "+r"(br0), "+r"(br1));
        const float bb0 = __uint_as_float(br0 << 16), bb1 = __uint_as_float(br1 << 16);
        named_arrive(wg ? 5 : 9, 256);
        mbar_wait(stf, stf_ph0);
        uint4* gdst = g_gfrag + ((size_t)((mrow >> 4) + warp_in_wg) * 40 + ((it >> 5) & 31) * 20) * 32;
#pragma unroll
        for (int q = 0; q < 5; q++) {
          if (q == 2) named_sync(wg ? 9 : 5, 256);
          const uint32_t piece = q < 2 ? qbuf + warp_in_wg * 4096 + q * 2048 : sbase + (wg * 4 + warp_in_wg) * 8192 + q * 2048 - 4096;
#pragma unroll
          for (int c = 4 * q; c < 4 * q + 4; c++) {
            const float* v = c < 8 ? &S[8 * c] : &T[8 * (c - 8)];
            asm volatile("st.shared.v4.b32 [%0], {%1,%2,%3,%4};" ::"r"(piece + (c & 3) * 512 + lane * 16), "r"(pack_bf16(v[0] + bb0, v[1] + bb0)),
                         "r"(pack_bf16(v[2] + bb1, v[3] + bb1)), "r"(pack_bf16(v[4] + bb0, v[5] + bb0)), "r"(pack_bf16(v[6] + bb1, v[7] + bb1)) : "memory");
          }
          fence_async_smem();
          __syncwarp();
          asm volatile(EL "cp.async.bulk.global.shared::cta.bulk_group [%0], [%1], 2048;\n}" ::"l"(gdst + q * 128), "r"(piece) : "memory");
        }
        asm volatile("{\n.reg .pred e;\nelect.sync _|e, 0xffffffff;\n@e cp.async.bulk.commit_group;\n@e cp.async.bulk.wait_group 0;\n"
                     "@e red.release.gpu.global.add.u32 [%0], 1;\n}" ::"l"(&g_cnt_g[(mrow >> 6) * 2 + ((it >> 5) & 31)]) : "memory");
        __syncwarp();
        break;
      } else if (type == IT_OP) {
        float S[64], Y[64];
        uint32_t prev = pp.so;
        mbar_wait(full0 + pp.so, pp.lap);
        WG_FENCE();
        mma_k64_first<1>(Y, sdesc(dbase + wg * 8192, 8192, pp.so), sdesc(dbase + 16384, 8192, pp.so));
        WG_COMMIT();
        pp.next<NA>();
        gemm_loop<1, NG, false>(Y, 1, NY, prev, pp, dbase, full0, empty_mapped, wg, lane);
        mbar_wait(full0 + pp.so, pp.lap);
        WG_FENCE();
        mma_k64_first<0>(S, sdesc(dbase + wg * 8192, 16, pp.so), sdesc(dbase + 16384, 8192, pp.so));
        WG_COMMIT();
        WG_WAIT(1);
        release_stage(empty_mapped, prev, lane);
        prev = pp.so;
        pp.next<NG>();
        gemm_loop<0, NG, false>(S, 1, HD / 64, prev, pp, dbase, full0, empty_mapped, wg, lane);
        fence_regs(Y);
        mbar_wait(ybar + wg * 8, 0);
        mbar_wait(full0 + pp.so, pp.lap);
        {
          const uint32_t xbuf = sbase + pp.so * (STAGE_BYTES / 8) + wg * 16384;
          const int mi = lane >> 3;
          const uint32_t rowaddr = xbuf + (warp_in_wg * 16 + (mi & 1) * 8 + (lane & 7)) * 128;
#pragma unroll
          for (int hf = 0; hf < 2; hf++) {
#pragma unroll
            for (int kk = 4 * hf; kk < 4 * hf + 4; kk++) {
              uint32_t g[4];
              asm volatile("ld.shared.v4.b32 {%0,%1,%2,%3}, [%4];" : "=r"(g[0]), "=r"(g[1]), "=r"(g[2]), "=r"(g[3])
                           : "r"(qbuf + warp_in_wg * 4096 + kk * 512 + lane * 16) : "memory");
#pragma unroll
              for (int q = 0; q < 4; q++) {
                Y[8 * kk + 2 * q] = silu_f(Y[8 * kk + 2 * q] + __uint_as_float(g[q] << 16));
                Y[8 * kk + 2 * q + 1] = silu_f(Y[8 * kk + 2 * q + 1] + __uint_as_float(g[q] & 0xffff0000u));
              }
            }
            if (hf == 0) { WG_WAIT(0); fence_regs(S); }
#pragma unroll
            for (int kk = 4 * hf; kk < 4 * hf + 4; kk++) {
              const uint32_t addr = rowaddr + hf * 8192 + (((((2 * kk) & 7) + (mi >> 1)) ^ (lane & 7)) << 4);
              uint32_t r[4];
              asm volatile("ldmatrix.sync.aligned.m8n8.x4.shared.b16 {%0,%1,%2,%3}, [%4];" : "=r"(r[0]), "=r"(r[1]), "=r"(r[2]), "=r"(r[3]) : "r"(addr) : "memory");
#pragma unroll
              for (int q = 0; q < 4; q++) {
                const int i = 8 * kk + 2 * q;
                r[q] = pack_bf16(fmaf(S[i], Y[i], __uint_as_float(r[q] << 16)), fmaf(S[i + 1], Y[i + 1], __uint_as_float(r[q] & 0xffff0000u)));
              }
              stmatrix_x4(addr, r[0], r[1], r[2], r[3]);
            }
            fence_async_smem();
            __syncwarp();
            asm volatile(EL "cp.async.bulk.tensor.2d.global.shared::cta.bulk_group [%0, {%2, %3}], [%1];\n}"
                         ::"l"(&p.tm_out), "r"(xbuf + hf * 8192 + (warp & 3) * 2048), "r"((int)((it >> 5) & 31) * 128 + hf * 64),
                           "r"(mrow + (warp & 3) * 16) : "memory");
          }
          asm volatile("{\n.reg .pred e;\nelect.sync _|e, 0xffffffff;\n@e cp.async.bulk.commit_group;\n@e cp.async.bulk.wait_group.read 0;\n}" ::: "memory");
          __syncwarp();
        }
        break;
      } else if (type == IT_M1) {
        const uint32_t stage0 = sbase + QB0_OFF;
        uint32_t cur = it;
#pragma unroll 1
        for (int n = 0;; n++) {
          const uint32_t nx = __shfl_sync(0xffffffffu, (uint32_t)items[ii + 1], 0);
          const bool last = (nx >> 13) != IT_M1;
          if ((n & 1) == wg) {
            float S[64], T[64];
            undef_regs(S); undef_regs(T);
            const int half = cur & 31;
            const int row = (half ? ((cur >> 10) & 7) * 256 + half * 128 - 128 + rank * 64 : (((cur >> 10) & 7) * 2 + rank) * 128) + r0;
            uint32_t br[4];
#pragma unroll
            for (int q = 0; q < 4; q++) br[q] = __ldg(reinterpret_cast<const unsigned short*>(p.b1) + min(row + (q & 1) * 8 + (q >> 1) * 64, FF - 1));
            uint32_t prev = SO_DUMMY;
            fence_regs(S); fence_regs(T);
            named_sync(1 + wg, 256);
#pragma unroll 1
            for (int ks = 0; ks < (half ? SEQ / 64 : 0); ks++) {
              mbar_wait(full0 + pp.so, pp.lap);
              WG_FENCE();
              mma_k64<1, false>(S, sdesc(dbase, 8192, pp.so), sdesc(dbase + 16384, 8192, pp.so), ks);
              WG_COMMIT();
              WG_WAIT(1);
              release_stage2(empty_mapped, prev, lane);
              prev = pp.so;
              pp.next<NG>();
            }
#pragma unroll 1
            for (int ks = 0; ks < (half ? 0 : SEQ / 64); ks++) {
              mbar_wait(full0 + pp.so, pp.lap);
              const uint64_t da = sdesc(dbase, 8192, pp.so), db = sdesc(dbase + 16384, 8192, pp.so);
              WG_FENCE();
              wgmma_ss_p<1, 1>(S, da, db, ks);     wgmma_ss_p<1, 1, 512>(T, da, db, ks);
              wgmma_ss<1, 1, 128, 128>(S, da, db); wgmma_ss<1, 1, 640, 128>(T, da, db);
              wgmma_ss<1, 1, 256, 256>(S, da, db); wgmma_ss<1, 1, 768, 256>(T, da, db);
              wgmma_ss<1, 1, 384, 384>(S, da, db); wgmma_ss<1, 1, 896, 384>(T, da, db);
              WG_COMMIT();
              WG_WAIT(1);
              release_stage2(empty_mapped, prev, lane);
              prev = pp.so;
              pp.next<NG>();
            }
            named_arrive(2 - wg, 256);
            if (last) named_arrive(9, 256);
            WG_WAIT(0);
            fence_regs(S);
            fence_regs(T);
            release_stage2(empty_mapped, prev, lane);
            fence_regs(br);
            uint32_t U[32];
#pragma unroll
            for (int i = 0; i < 32; i++) { const float bb = __uint_as_float(br[i & 1] << 16); U[i] = pack_bf16(S[2 * i] + bb, S[2 * i + 1] + bb); }
            mbar_wait(stf0, stf_ph0);
            stage_tile(U, stage0, warp_in_wg, lane);
#pragma unroll
            for (int i = 0; i < 32; i++) { const float bb = __uint_as_float(br[2 + (i & 1)] << 16); U[i] = pack_bf16(T[2 * i] + bb, T[2 * i + 1] + bb); }
            mbar_wait(stf0 + 16, stf_ph0);
            stage_tile(U, stage0 + 16384, warp_in_wg, lane);
            __syncwarp();
            if (last) { named_arrive(5, 256); gpend = 1; }
            else {
              const uint32_t ew = stage0 + warp_in_wg * 2048 + lane * 4;
#pragma unroll 1
              for (int k = 0; k < 64; k++) {
                const uint32_t ad = ew + (k >> 4) * 8192 + (k & 15) * 128;
                uint32_t v;
                asm volatile("ld.shared.b32 %0, [%1];" : "=r"(v) : "r"(ad) : "memory");
                v = pack_bf16(gelu_f(__uint_as_float(v << 16)), gelu_f(__uint_as_float(v & 0xffff0000u)));
                asm volatile("st.shared.b32 [%0], %1;" ::"r"(ad), "r"(v) : "memory");
              }
              fence_async_smem();
              named_arrive(6, 160);
              named_arrive(7, 160);
            }
          } else {
            pp.lap ^= 1;
            pp.next<NG>(); pp.next<NG>();
            if (last && wg == 1) { named_sync(2, 256); named_arrive(1, 256); }
            if (last) { named_sync(9, 256); gpend = 2; }
          }
          stf_ph0 ^= 1;
          if (last) break;
          ii++;
          cur = nx;
        }
      } else {
        uint32_t P0[32], P1[32];
        SmState st;
        uint32_t qaddr = dbase + QB0_OFF + wg * 16384;
        if (__builtin_expect(type == IT_ATTN1, 0)) {
          float S[64];
          undef_regs(S);
          uint32_t prev = SO_DUMMY;
          gemm_loop<0, NG, true, 0>(S, 0, DM / 64, prev, pp, dbase, full0, empty_mapped, wg, lane);
          pack_scaled(S, P1, 1.f, 1.f);
          mbar_wait(stf, stf_ph0);
          stage_tile(P1, qbuf, warp_in_wg, lane);
          fence_async_smem();
        } else {
          float S[64], O[64];
          uint32_t sa = pp.so, sb, sc;
          {
            mbar_wait(full0 + pp.so, pp.lap); pp.next<NG>();
            if (after_attn) pp.enter_attn();
            const uint64_t xa = sdesc(dbase + wg * 8192, 16, sa);
            WG_FENCE();
            mma_k64_first<0>(O, xa, sdesc(dbase + 16384, 8192, sa));
            WG_COMMIT();
            sb = pp.so;
            mbar_wait(full0 + pp.so, pp.lap); pp.next<NG>();
            WG_FENCE();
            mma_k64_first<0>(S, xa, sdesc(dbase, 16384, sb));
            WG_COMMIT();
          }
#pragma unroll 1
          for (int m = 0;; m++) {
            sc = pp.so;
            mbar_wait(full0 + pp.so, pp.lap); pp.next<NG>();
            const uint64_t xc = sdesc(dbase + wg * 8192, 16, sc);
            WG_FENCE();
            qp_group(S, xc, sdesc(dbase + 8192, 16384, sb));
            WG_COMMIT();
            WG_WAIT(1);
            release_stage(empty_mapped, sa, lane);
            WG_FENCE();
            qp_group(O, xc, sdesc(dbase + 16384, 8192, sc));
            WG_COMMIT();
            if (m == 4) named_arrive(2 - wg, 256);
            if (gpend && m < 4) {
              if (m == 0 && gpend == 2) named_sync(5, 256);
              gelu_inplace<2>(qbuf + warp_in_wg * 2048 + lane * 16 + (m >> 1) * 8192 + (m & 1) * 1024);
              if (m == 3) { fence_async_smem(); named_arrive(6 + wg, 160); }
            }
            WG_WAIT(1);
            release_stage(empty_mapped, sb, lane);
            if (m == 4) break;
            sa = pp.so;
            mbar_wait(full0 + pp.so, pp.lap); pp.next<NG>();
            const uint64_t xa = sdesc(dbase + wg * 8192, 16, sa);
            if (m == 3) named_sync(1 + wg, 256);
            WG_FENCE();
            qp_group(O, xa, sdesc(dbase + 16384, 8192, sa));
            WG_COMMIT();
            WG_WAIT(1);
            release_stage(empty_mapped, sc, lane);
            sb = pp.so;
            mbar_wait(full0 + pp.so, pp.lap); pp.next<NG>();
            WG_FENCE();
            qp_group(S, xa, sdesc(dbase, 16384, sb));
            WG_COMMIT();
          }
          gpend = 0;
          fence_regs(S);
          pack_scaled(S, P0, 1.f, 1.f);
          mbar_wait(stf, stf_ph0);
          stage_tile(P0, qbuf, warp_in_wg, lane);
          fence_async_smem();
          WG_WAIT(0);
          fence_regs(O);
          release_stage(empty_mapped, sc, lane);
          pack_scaled(O, P1, 1.f, 1.f);
        }
        pp.enter_attn();
        float S[64], O[64];
        {
          named_sync(3 + wg, 128);
          const uint32_t ks = pp.so;
          mbar_wait(full0 + pp.so, pp.lap); pp.next<NA>();
          named_sync(1 + wg, 256);
          WG_FENCE();
          issue_qk(S, make_desc(qaddr, 16), sdesc(dbase, 16, ks));
          WG_COMMIT();
          named_arrive(2 - wg, 256);
          undef_regs(O);
          fence_regs(O);
          WG_WAIT(0);
          fence_regs(S);
          release_stage(empty_mapped, ks, lane);
        }
        {
          float f0, f1;
          st.m0 = st.m1 = st.l0 = st.l1 = 0.f; st.sub = false;
          softmax_block(S, P0, st, true, f0, f1);
        }
        const int npair = type == IT_ATTN2 ? 16 : 8;
#pragma unroll 1
        for (int j = 0;; j++) {
          attn_step<false>(S, O, P0, P1, qaddr, st, j & 7, pp, dbase, full0, empty_mapped, wg, lane, (j & 7) == 0,
                           j ? qbuf : qbuf - STAGE_BYTES, j ? 6 + wg : 0, j == npair - 1);
          if (j == npair - 1) break;
          if (j == 7) { qaddr -= STAGE_BYTES; stf_ph0 ^= 1; }
          attn_step<true>(S, O, P1, P0, qaddr, st, 1, pp, dbase, full0, empty_mapped, wg, lane, j == 7, 0, 0);
        }
        {
          it = __shfl_sync(0xffffffffu, (uint32_t)items[ii + 1], 0);
          const uint32_t vs = pp.so;
          mbar_wait(full0 + pp.so, pp.lap); pp.next<NA>();
          named_sync(1 + wg, 256);
          WG_FENCE();
          issue_pv(O, P1, sdesc(dbase, 16384, vs), 1, 2 - wg);
          WG_COMMIT();
          const float i0 = __fdividef(1.f, quad_sum(st.l0)), i1 = __fdividef(1.f, quad_sum(st.l1));
          WG_WAIT(0);
          fence_regs(O);
          fence_regs(P1);
          release_stage(empty_mapped, vs, lane);
          pack_scaled(O, P0, i0, i1);
          mbar_wait(stf, stf_ph0);
          stage_tile(P0, qbuf, warp_in_wg, lane);
          fence_async_smem();
          named_arrive(6 + wg, 160);
          stf_ph0 ^= 1;
        }
      }
      if (type > IT_ATTN2) it = __shfl_sync(0xffffffffu, (uint32_t)items[ii + 1], 0);
      after_attn = type <= IT_ATTN2;
    }
    if (wg == 0) named_sync(1, 256);
  } else {
    asm volatile("setmaxnreg.dec.sync.aligned.u32 24;");
    const int pw = warp & 3;
    if (pw == 0) {
      unsigned ep = 0;
      if (lane == 0) ep = atomicAdd(&g_epoch[blockIdx.x * 8], 1u) + 1;
      if (lane == 0) *epoch_s = ep;
      ep = __shfl_sync(0xffffffffu, ep, 0);
      Pipe pp; pp.so = st0 * 8; pp.lap = 1;
      uint32_t x5 = 0;
      uint32_t ln_ok = 0, u_ok = 0, o_ok = 0;
      bool short_lap = false;
      const unsigned* ln_ptr = &g_cnt_ln[lane * 32];
      const unsigned* u_ptr = &g_cnt_u[(lane < 7 ? lane : 0) * 32];
#define ACQ_G() mbar_wait(empty0 + pp.so, pp.so == 8 * NA ? pp.lap ^ x5 : pp.lap); \
                const uint32_t fb = full0 + pp.so, sb = sbase + pp.so * (STAGE_BYTES / 8)
#define ACQ_A() mbar_wait(empty0 + pp.so, pp.lap); \
                const uint32_t fb = full0 + pp.so, sb = sbase + pp.so * (STAGE_BYTES / 8)
#pragma unroll 1
      for (int ii = 0; ii < MAXITEMS; ii++) {
        const uint32_t it = __shfl_sync(0xffffffffu, (uint32_t)items[ii], 0);
        const int type = it >> 13, a = (it >> 10) & 7, b = (it >> 5) & 31, c = it & 31;
        if (type == IT_NONE) break;
        const int arow = (a * 2 + rank) * 128;
        if (type == IT_M2) {
#pragma unroll 1
          for (int k0 = NY * 64; k0 < FF; k0 += 64) {
            u_ok = mask_wait(u_ok, 1u << (k0 >> 8), 127u, u_ptr, ep * 20);
#pragma unroll
            for (int q = 0; q < 2; q++) {
              ACQ_G();
              w_expect(fb, 28672);
              w_load<0, 1>(sb, &p.tm_w2, arow, k0 + q * 32, fb);
              w_load<0, 1>(sb + 4096, &p.tm_w2, arow + 64, k0 + q * 32, fb);
              w_load<1, 1>(sb + 8192 + rank * 8192, &p.tm_ut, b * 320 + rank * 128, k0 + q * 32, fb);
              w_load<1, 1>(sb + 12288 + rank * 8192, &p.tm_ut, b * 320 + rank * 128 + 64, k0 + q * 32, fb);
              if (q == rank) w_load<1, 1>(sb + 24576, &p.tm_ut, b * 320 + 256, k0 + q * 32, fb);
              pp.next<NG>();
              if (q == 0 && k0 == NY * 64) pp.enter_attn();
            }
          }
        } else if (type == IT_OP) {
          const unsigned* o_ptr = &g_cnt_o[(a * 2 + rank) * 32 + lane];
          mask_wait(u_ok, (2u << ((NY - 1) >> 2)) - 1, 127u, u_ptr, ep * 20);
#pragma unroll 1
          for (int k0 = 0; k0 < NY * 64; k0 += 64) {
            ACQ_G();
            w_expect(fb, STAGE_BYTES);
            w_load<0, 1>(sb, &p.tm_w2b, arow, k0, fb);
            w_load<0, 1>(sb + 8192, &p.tm_w2b, arow + 64, k0, fb);
            w_load<1, 1>(sb + 16384 + rank * 8192, &p.tm_ut_st, b * 128 + rank * 64, k0, fb);
            pp.next<NG>();
            if (k0 == 0) pp.enter_attn();
            if (k0 == 64) o_ok = mask_wait(o_ok, 1u << p.horder[a * 32], 0xffffffffu, o_ptr, ep * 2);
          }
#pragma unroll 1
          for (int hi = 0; hi < NH; hi++) {
            const int h = p.horder[a * 32 + hi];
            o_ok = mask_wait(o_ok, 1u << h, 0xffffffffu, o_ptr, ep * 2);
#pragma unroll
            for (int q = 0; q < 2; q++) {
              ACQ_G();
              w_expect(fb, STAGE_BYTES);
              w_load<0, 1>(sb, &p.tm_o_ld, h * DH + q * 64, arow, fb);
              w_load<1, 1>(sb + 16384 + rank * 8192, &p.tm_wo, b * 128 + rank * 64, h * DH + q * 64, fb);
              pp.next<NG>();
            }
            if (hi == 16) {
              for (int q = 0; q < 4; q++)
                asm volatile(EL "cp.async.bulk.prefetch.tensor.2d.L2.global [%0, {%1, %2}];\n}" ::"l"(&p.tm_x), "r"(b * 128 + (q & 1) * 64), "r"(arow + (q >> 1) * 64) : "memory");
            }
          }
          {
            ACQ_G();
            w_expect(fb, STAGE_BYTES);
            for (int q = 0; q < 4; q++) w_load<0, 0>(sb + q * 8192, &p.tm_x, b * 128 + (q & 1) * 64, arow + (q >> 1) * 64, fb);
          }
        } else if (type == IT_M1) {
          ln_ok = mask_wait(ln_ok, 0xffff0000u, 0xffffffffu, ln_ptr, ep * 8);
          const int frow = c ? a * 256 + c * 128 - 128 + rank * 64 : arow;
#pragma unroll 1
          for (int k0 = 0; k0 < SEQ; k0 += 64) {
            ACQ_G();
            w_expect(fb, c ? 24576 : STAGE_BYTES);
            w_load<0, 1>(sb, &p.tm_w1, frow, k0, fb);
            if (!c) w_load<0, 1>(sb + 8192, &p.tm_w1, frow + 64, k0, fb);
            w_load<1, 0>(sb + 16384 + rank * 8192, &p.tm_h, b * 128 + rank * 64, k0, fb);
            pp.next<NG>();
          }
        } else {
          int skip = ii == 0 ? WPRE : 0;
          ln_ok = mask_wait(ln_ok, 1u << (a * 2 + rank), 1u << (a * 2 + rank), ln_ptr, ep * 8);
#pragma unroll 1
          for (int k0 = 0; k0 < DM; k0 += 64) {
            {
              ACQ_G();
              if (--skip < 0) {
                w_expect(fb, STAGE_BYTES);
                w_load<1, 1>(sb + 16384 + rank * 8192, &p.tm_wq, c * DH + rank * 64, k0, fb);
              }
              w_load<0, 0>(sb, &p.tm_xn, k0, arow, fb);
              if (ii == 0 && k0 == GOK) w_expect(gobar, 0);
              pp.next<NG>();
              if (k0 == 0 && short_lap) pp.enter_attn();
            }
            if (type == IT_ATTN2 && (k0 & 64) == 0) {
              ACQ_G();
              if (--skip < 0) {
                w_expect(fb, STAGE_BYTES);
                w_load<1, 1>(sb + rank * 16384, &p.tm_wq, b * DH + rank * 64, k0, fb);
                w_load<1, 1>(sb + rank * 16384 + 8192, &p.tm_wq, b * DH + rank * 64, k0 + 64, fb);
              }
              pp.next<NG>();
            }
          }
          const uint32_t nx = __shfl_sync(0xffffffffu, (uint32_t)items[ii + 1], 0);
          short_lap = (nx >> 13) != IT_M1;
          const uint32_t lap0 = pp.lap;
          pp.enter_attn();
          const uint32_t odd = (lap0 ^ pp.lap ^ ((pp.so / 8 + (type == IT_ATTN2 ? 64 : 32) + (short_lap ? 1 : 0)) / NA)) & 1;
          x5 ^= odd ^ 1;
          const int nblk = type == IT_ATTN2 ? 32 : 16;
          const char* pf0 = reinterpret_cast<const char*>(a < 4 ? p.kc : p.vc) + ((a & 3) * 2 + rank) * 4096;
          const char* pf = pf0 + (size_t)(b * 16 + PFD) * 32768;
          int row = b * SEQ;
#define LOAD_KV(tm, r) { ACQ_A(); w_expect(fb, STAGE_BYTES); w_load<1, 1>(sb + rank * 16384, tm, rank * 64, r, fb); pp.next<NA>(); }
          LOAD_KV(&p.tm_k, row)
#pragma unroll 1
          for (int seg = 0; seg < 3; seg++) {
            const int n = seg == 0 ? 4 : seg == 1 ? nblk - PFD - 4 : PFD - 1;
#pragma unroll 1
            for (int i = 0; i < n; i++) {
              LOAD_KV(&p.tm_k, row + 128)
              LOAD_KV(&p.tm_v, row)
              row += 128;
              if (pf) { w_prefetch_ef(pf); pf += 32768; }
            }
            if (seg == 0) {
              if (odd) w_expect(full0 + 8 * NA, 0);
              ln_ok = mask_wait(ln_ok, 0xffffffffu, 0xffffffffu, ln_ptr, ep * 8);
            } else if (seg == 1) {
              pf = (nx >> 13) == IT_ATTN2 ? pf0 + (size_t)((nx >> 5) & 31) * 16 * 32768 : nullptr;
            }
          }
          LOAD_KV(&p.tm_v, row)
          if (pf) w_prefetch_ef(pf);
        }
      }
    } else {
      if (pw == 1) {
        const uint32_t it = items[0];
        const int type = it >> 13, a = (it >> 10) & 7, b = (it >> 5) & 31, c = it & 31, k = lane;
        if (type == IT_ATTN2) {
          if ((k & 7) != a) {}
          else if (k < 20) tma_prefetch(&p.tm_wq, ((k & 1) ? c : b) * DH + rank * 64, (k >> 1) * 64);
          const char* pfb = reinterpret_cast<const char*>(a < 4 ? p.kc : p.vc) + ((a & 3) * 2 + rank) * 4096;
          if (lane >= 24 && lane < 24 + PFD) l2_prefetch_ef(pfb + (size_t)(b * 16 + lane - 24) * 32768);
        }
        __syncwarp();
      } else if (pw == 2 && lane < 15) {
        asm volatile("prefetch.tensormap [%0];" ::"l"(&p.tm_xn + lane) : "memory");
      }
      __syncwarp();
      asm volatile("barrier.cluster.wait.aligned;" ::: "memory");
      if (pw == 3) {
       if (lane == 0) {
        if (ln_cta) {
          mbar_wait(lnb0 + 8, 0);
          mbar_wait(gobar, 0);
          bulk_store(g_h + (size_t)blockIdx.x * 16 * DM, sbase + QB0_OFF, 16 * DM * 2);
          bulk_commit();
          bulk_wait_read0();
        }
        mbar_arrive_local(stf0);
        mbar_arrive_local(stf0 + 16);
        if (ln_cta) {
          bulk_wait0();
          red_release(&g_cnt_ln[(16 + (blockIdx.x >> 3)) * 32], 1);
        }
       }
       __syncwarp();
      } else {
        const int w = pw - 1;
#pragma unroll 1
        for (int ii = 0; ii < MAXITEMS; ii++) {
          const uint32_t it = __shfl_sync(0xffffffffu, (uint32_t)items[ii], 0);
          const int type = it >> 13, a = (it >> 10) & 7, b = (it >> 5) & 31, c = it & 31;
          if (type == IT_NONE) break;
          const bool half = type == IT_M1 && c;
          const int mrow = half ? (w ? FF : a * 256 + c * 128 - 128 + rank * 64) : (a * 2 + rank) * 128 + w * 64;
          const uint32_t buf0 = sbase + QB0_OFF + w * 16384;
          if (type == IT_M2) continue;
          if (type == IT_OP) {
            if (lane == 0) {
              const unsigned ep = *epoch_s;
              if (b <= 2) flag_wait(&g_cnt_g[(mrow >> 6) * 2], ep * 4);
              if (b >= 2) flag_wait(&g_cnt_g[(mrow >> 6) * 2 + 1], ep * 4);
              mbar_expect_tx(ybar + w * 8, 16384);
              for (int ww = 0; ww < 4; ww++)
                asm volatile("cp.async.bulk.shared::cluster.global.mbarrier::complete_tx::bytes [%0], [%1], 4096, [%2];"
                             ::"r"(buf0 + ww * 4096), "l"(g_gfrag + ((size_t)((mrow >> 4) + ww) * 40 + b * 8) * 32), "r"(ybar + w * 8) : "memory");
            }
            __syncwarp();
            continue;
          }
          const CUtensorMap* tm = type <= IT_ATTN2 ? &p.tm_o_st : &p.tm_ut_st;
          const int nq = type == IT_ATTN2 ? 2 : 1;
#pragma unroll 1
          for (int q = 0; q < nq; q++) {
            const int col = q ? c : b;
            named_sync(6 + w, 160);
            if (lane == 0) {
              if (type != IT_M1 || mrow < FF) {
                tma_store(tm, buf0, col * 128, mrow);
                tma_store(tm, buf0 + 8192, col * 128 + 64, mrow);
              }
              bulk_commit();
              bulk_wait0();
              mbar_arrive_local(stf0 + w * 16);
              if (!(half && w))
                red_release(type == IT_M1 ? &g_cnt_u[a * 32] : &g_cnt_o[(a * 2 + rank) * 32 + col], 1);
            }
            __syncwarp();
          }
        }
      }
    }
  }
  asm volatile("barrier.cluster.arrive.relaxed.aligned;\nbarrier.cluster.wait.aligned;" ::: "memory");
}

typedef CUresult (*EncodeFn)(CUtensorMap*, CUtensorMapDataType, cuuint32_t, void*, const cuuint64_t*, const cuuint64_t*,
                             const cuuint32_t*, const cuuint32_t*, CUtensorMapInterleave, CUtensorMapSwizzle,
                             CUtensorMapL2promotion, CUtensorMapFloatOOBfill);

void make_map(EncodeFn enc, CUtensorMap* tm, const void* ptr, uint64_t rows, uint64_t cols, uint32_t box_rows) {
  cuuint64_t dims[2] = {cols, rows};
  cuuint64_t strides[1] = {cols * 2};
  cuuint32_t box[2] = {64, box_rows};
  cuuint32_t es[2] = {1, 1};
  enc(tm, CU_TENSOR_MAP_DATA_TYPE_BFLOAT16, 2, const_cast<void*>(ptr), dims, strides, box, es, CU_TENSOR_MAP_INTERLEAVE_NONE,
      CU_TENSOR_MAP_SWIZZLE_128B, CU_TENSOR_MAP_L2_PROMOTION_L2_128B, CU_TENSOR_MAP_FLOAT_OOB_FILL_NONE);
}

void build_schedule(Params& p) {
  memset(p.items, 0, sizeof(p.items));
  auto gpc = [](int c) { return c < 4 ? 0 : c < 36 ? (c - 4) % 8 : c < 64 ? 1 + (c - 36) % 7 : c - 58; };
  int cls[NCLUSTER];
  for (int c = 0; c < NCLUSTER; c++) cls[c] = c < 4 ? 1 : c < 44 ? 0 : c < 46 ? 2 : c < 54 ? 3 : 1;
  auto mk = [](int t, int a, int b, int c) { return (uint16_t)((t << 13) | (a << 10) | (b << 5) | c); };
  int m1 = 0, nhalf = 0;
  for (int r = 0; r < 4; r++)
    for (int c = 0; c < NCLUSTER; c++) {
      if (cls[c] == 3) { p.items[c * MAXITEMS + 1 + r] = mk(IT_M1, m1 / 5, m1 % 5, 0); m1++; }
      if (cls[c] == 2 && r == 3) {
        p.items[c * MAXITEMS + 1] = mk(IT_M1, 6, 4, ++nhalf);
        p.items[c * MAXITEMS + 2] = mk(IT_M1, m1 / 5, m1 % 5, 0); m1++;
      }
    }
  struct Slot { int t, c, pos, n; };
  Slot slots[2 * NCLUSTER];
  int ns = 0, nb[8] = {0};
  for (int c = 0; c < NCLUSTER; c++) {
    slots[ns++] = Slot{0, c, 0, cls[c] == 3 ? 1 : 2};
    slots[ns++] = Slot{cls[c] == 3 ? 113 : cls[c] == 2 ? 108 : 79, c, cls[c] == 3 ? 5 : cls[c] == 2 ? 3 : 1, 2};
    if (cls[c] == 0) {
      int a = gpc(c);
      while (nb[a] == 5) a = (a + 7) & 7;
      p.items[c * MAXITEMS + 2] = mk(IT_OP, a, nb[a]++, 0);
    }
  }
  {
    int n2[8] = {0};
    for (int pass = 0; pass < 2; pass++)
      for (int c = NCLUSTER - 1; c >= 0; c--)
        if (cls[c] == 1 && !p.items[c * MAXITEMS + 2]) {
          int a = gpc(c);
          if (n2[a] == 2) { if (!pass) continue; while (n2[a] == 2) a = (a + 1) & 7; }
          p.items[c * MAXITEMS + 2] = mk(IT_M2, a, n2[a]++, 0);
        }
  }
  for (int i = 1; i < ns; i++) {
    Slot s = slots[i]; int j = i - 1;
    while (j >= 0 && slots[j].t > s.t) { slots[j + 1] = slots[j]; j--; }
    slots[j + 1] = s;
  }
  int d = 0, sg = 0;
  int tdone[8][32];
  for (int i = 0; i < ns;) {
    int e = i, nd = 0;
    while (e < ns && slots[e].t == slots[i].t) nd += slots[e++].n == 2;
    bool used[128] = {false}, done[2 * NCLUSTER] = {false};
    for (int pass = 0; pass < 2; pass++)
      for (int k = i; k < e; k++) {
        const Slot& s = slots[k];
        if (done[k]) continue;
        if (s.n == 2) {
          int q = d;
          while (q < d + nd && (used[q] || (!pass && (q & 7) != gpc(s.c)))) q++;
          if (q == d + nd) continue;
          used[q] = true;
          const int a = q & 7, hp = q >> 3;
          p.items[s.c * MAXITEMS + s.pos] = mk(IT_ATTN2, a, 2 * hp, 2 * hp + 1);
          tdone[a][2 * hp] = s.t + 43; tdone[a][2 * hp + 1] = s.t + 77;
        } else {
          const int a = 4 + (sg & 3), h = 30 + (sg >> 2);
          p.items[s.c * MAXITEMS + s.pos] = mk(IT_ATTN1, a, h, h);
          tdone[a][h] = s.t + 40;
          sg++;
        }
        done[k] = true;
      }
    d += nd;
    i = e;
  }
  for (int a = 0; a < 8; a++) {
    uint8_t* o = &p.horder[a * 32];
    for (int h = 0; h < 32; h++) {
      int j = h - 1;
      while (j >= 0 && tdone[a][o[j]] > tdone[a][h]) { o[j + 1] = o[j]; j--; }
      o[j + 1] = (uint8_t)h;
    }
  }
}

}


extern "C" void kernel_launch(void* const* d_in, const int* in_sizes, int n_in, void* d_out, int out_size) {
  (void)in_sizes; (void)n_in; (void)out_size;
  static EncodeFn enc = nullptr;
  if (!enc) {
    void* fn = nullptr;
    cudaDriverEntryPointQueryResult qr;
    cudaGetDriverEntryPoint("cuTensorMapEncodeTiled", &fn, cudaEnableDefault, &qr);
    enc = (EncodeFn)fn;
    cudaFuncSetAttribute(mega_kernel, cudaFuncAttributeMaxDynamicSharedMemorySize, SMEM_BYTES);
  }
  void *xn, *h, *o, *ut;
  cudaGetSymbolAddress(&xn, g_xn); cudaGetSymbolAddress(&h, g_h); cudaGetSymbolAddress(&o, g_o);
  cudaGetSymbolAddress(&ut, g_ut);
  Params p;
  make_map(enc, &p.tm_xn, xn, SEQ, DM, 128);
  make_map(enc, &p.tm_wq, d_in[3], DM, HD, 64);
  make_map(enc, &p.tm_k, d_in[1], (uint64_t)NH * SEQ, DH, 128);
  make_map(enc, &p.tm_v, d_in[2], (uint64_t)NH * SEQ, DH, 128);
  make_map(enc, &p.tm_o_st, o, SEQ, HD, 64);
  make_map(enc, &p.tm_o_ld, o, SEQ, HD, 128);
  make_map(enc, &p.tm_wo, d_in[4], HD, DM, 64);
  make_map(enc, &p.tm_w1, d_in[6], SEQ, FF, 64);
  make_map(enc, &p.tm_h, h, SEQ, DM, 64);
  make_map(enc, &p.tm_ut_st, ut, FF, DM, 64);
  make_map(enc, &p.tm_ut, ut, FF, DM, 32);
  make_map(enc, &p.tm_w2, d_in[8], FF, SEQ, 32);
  make_map(enc, &p.tm_out, d_out, SEQ, DM, 16);
  make_map(enc, &p.tm_w2b, d_in[8], FF, SEQ, 64);
  make_map(enc, &p.tm_x, d_in[0], SEQ, DM, 64);
  p.x = (const bf16*)d_in[0]; p.b1 = (const bf16*)d_in[7]; p.b2 = (const bf16*)d_in[9];
  p.kc = (const bf16*)d_in[1]; p.vc = (const bf16*)d_in[2];
  build_schedule(p);
  mega_kernel<<<2 * NCLUSTER, 384, SMEM_BYTES, cudaStreamPerThread>>>(p);
}
```
